```python
import torch

def _softmax(x, axis=-1):
    return torch.softmax(x, dim=axis)

def _gelu(x):
    return torch.nn.functional.gelu(x, approximate='tanh')

def _silu(x):
    return torch.nn.functional.silu(x)

def _sigmoid(x):
    return torch.sigmoid(x)

def _layernorm(x, axis=-1, eps=1e-05):
    m = x.mean(dim=axis, keepdim=True)
    v = x.var(dim=axis, keepdim=True, unbiased=False)
    return (x - m) / torch.sqrt(v + eps)

def _scatter_add(tgt, idx, src, axis=0):
    return tgt.clone().index_add_(axis, idx, src)

def _segment_sum(src, seg, n):
    out = torch.zeros((n,) + src.shape[1:], dtype=src.dtype)
    return out.index_add_(0, seg, src)

def _pad(x, pw):
    flat = tuple((v for pair in reversed(pw) for v in pair))
    return torch.nn.functional.pad(x, flat)
kernel_name = 'gated_mix__ssm_conv_h3__memory_aug_recurrent_mem_tr__prompt'

def setup_inputs():

    _w = lambda a: (lambda t: t.to(torch.bfloat16) if t.is_floating_point() else t)(torch.as_tensor(a))

    def _A_setup():
        B, S, D = (1, 2048, 1024)
        ks = 4
        return {'q': _w((lambda *s: torch.randn(*s, dtype=torch.bfloat16) * 0.05)(B, S, D)), 'k': _w((lambda *s: torch.randn(*s, dtype=torch.bfloat16) * 0.4)(B, S, D)), 'v': _w((lambda *s: torch.randn(*s, dtype=torch.bfloat16) * 0.4)(B, S, D)), 'shift_k': _w((lambda *s: torch.randn(*s, dtype=torch.bfloat16) * 0.4)(D, ks) * 0.5), 'ssm_k': _w((lambda *s: torch.randn(*s, dtype=torch.bfloat16) * 0.4)(D, S) * (1.0 / S ** 0.5)), 'ssm_D': _w((lambda *s: torch.randn(*s, dtype=torch.bfloat16) * 0.4)(D))}
    _A_in = _A_setup()

    def _B_setup():
        B, S, Dm = (1, 2048, 1024)
        H, Dh = (32, 128)
        M, seg = (8, 32)
        seg = min(seg, S)
        S = S // seg * seg
        return {'x': _w((lambda *s: torch.randn(*s, dtype=torch.bfloat16) * 0.05)(B, S, Dm)), 'mem0': _w((lambda *s: torch.randn(*s, dtype=torch.bfloat16) * 0.4)(B, M, Dm)), 'Wq': _w((lambda *s: torch.randn(*s, dtype=torch.bfloat16) * 6.4)(Dm, H, Dh) * Dm ** (-0.5)), 'Wk': _w((lambda *s: torch.randn(*s, dtype=torch.bfloat16) * 6.4)(Dm, H, Dh) * Dm ** (-0.5)), 'Wv': _w((lambda *s: torch.randn(*s, dtype=torch.bfloat16) * 0.4)(Dm, H, Dh) * Dm ** (-0.5)), 'Wo': _w((lambda *s: torch.randn(*s, dtype=torch.bfloat16) * 0.4)(H, Dh, Dm) * (H * Dh) ** (-0.5)), 'seg_len': seg}
    _B_in = _B_setup()
    return {'A_q': _A_in['q'], 'A_k': _A_in['k'], 'A_v': _A_in['v'], 'A_shift_k': _A_in['shift_k'], 'A_ssm_k': _A_in['ssm_k'], 'A_ssm_D': _A_in['ssm_D'], 'B_x': _B_in['x'], 'B_mem0': _B_in['mem0'], 'B_Wq': _B_in['Wq'], 'B_Wk': _B_in['Wk'], 'B_Wv': _B_in['Wv'], 'B_Wo': _B_in['Wo'], 'B_seg_len': _B_in['seg_len'], 'gate_w': _w((lambda *s: torch.randn(*s, dtype=torch.bfloat16) * 0.05)(1024) * 16.0)}

def reference(A_q, A_k, A_v, A_shift_k, A_ssm_k, A_ssm_D, B_x, B_mem0, B_Wq, B_Wk, B_Wv, B_Wo, B_seg_len, gate_w):

    def _A_ref(q, k, v, shift_k, ssm_k, ssm_D):
        B, S, D = q.shape
        ks = shift_k.shape[-1]
        k_pad = _pad(k, ((0, 0), (ks - 1, 0), (0, 0)))
        k_shift = torch.zeros_like(k)
        for t in range(ks):
            k_shift = k_shift + k_pad[:, t:t + S, :] * shift_k[:, ks - 1 - t][None, None, :]
        kv = k_shift * v
        L = 2 * S
        kv_pad = _pad(kv, ((0, 0), (0, S), (0, 0)))
        kf_pad = _pad(ssm_k, ((0, 0), (0, S)))
        kv_f = (lambda x, axes=(-2, -1): torch.fft.rfft2(x.float(), dim=axes))(kv_pad[:, None, :, :], axes=(1, 2))
        kf_f = (lambda x, axes=(-2, -1): torch.fft.rfft2(x.float(), dim=axes))(kf_pad[:, None, :], axes=(1, 2))
        kf_f = (lambda x, *d: x.permute(*d))(kf_f, 1, 2, 0)
        y_f = kv_f * kf_f[None, :, :, :]
        y = (lambda x, s, axes=(-2, -1): torch.fft.irfft2(x, s=s, dim=axes).to(torch.bfloat16))(y_f, (1, L), axes=(1, 2))[:, 0, :S, :]
        y = y + kv * ssm_D[None, None, :]
        return q * y

    def _B_ref(x, mem0, Wq, Wk, Wv, Wo, seg_len):
        B, S, Dm = x.shape
        H, Dh = (Wq.shape[1], Wq.shape[2])
        M = mem0.shape[1]
        scale = Dh ** (-0.5)
        n_seg = S // seg_len
        L = M + seg_len
        idx = torch.arange(L)
        mask = (idx[:, None] < M) | (idx[:, None] >= idx[None, :])
        mem = mem0
        outs = []
        for s in range(n_seg):
            xs = x[:, s * seg_len:(s + 1) * seg_len, :].clone()
            h = torch.concatenate([mem, xs], axis=1)
            q = torch.einsum('btd,dhe->bhte', h, Wq)
            k = torch.einsum('btd,dhe->bhte', h, Wk)
            v = torch.einsum('btd,dhe->bhte', h, Wv)
            scores = torch.einsum('bhqe,bhke->bhqk', q, k) * scale
            scores = torch.where(mask[None, None], scores, -1000000000.0)
            p = _softmax(scores, axis=-1)
            o = torch.einsum('bhqk,bhke->bhqe', p, v)
            o = torch.einsum('bhte,hed->btd', o, Wo)
            mem = o[:, :M, :].clone()
            outs.append(o[:, M:, :])
        return torch.concatenate(outs, axis=1)
    x = A_q
    g = _sigmoid((x * gate_w).sum(-1, keepdims=True))
    a = _A_ref(x, A_k, A_v, A_shift_k, A_ssm_k, A_ssm_D)
    b = _B_ref(x, B_mem0, B_Wq, B_Wk, B_Wv, B_Wo, B_seg_len)
    return g * a + (1 - g) * b
```

```cpp
#include <cuda_runtime.h>
#include <cuda_bf16.h>
#include <cuda.h>
#include <stdint.h>
#include <string.h>

typedef __nv_bfloat16 bf16;

constexpr int SEQ = 2048, DM = 1024, NH = 32, DH = 128, HD = NH * DH, MEM = 8, SEG = 32, NSEG = SEQ / SEG;

__device__ __forceinline__ uint32_t smem_u32(const void* p) { return (uint32_t)__cvta_generic_to_shared(p); }
__device__ __forceinline__ void wg_fence() { asm volatile("wgmma.fence.sync.aligned;\n" ::: "memory"); }
__device__ __forceinline__ void wg_commit() { asm volatile("wgmma.commit_group.sync.aligned;\n" ::: "memory"); }
template <int N> __device__ __forceinline__ void wg_wait() { asm volatile("wgmma.wait_group.sync.aligned %0;\n" ::"n"(N) : "memory"); }
template <int N> __device__ __forceinline__ void fence_regs(float (&a)[N]) {
#pragma unroll
  for (int i = 0; i < N; i++) asm volatile("" : "+f"(a[i])::"memory");
}
__device__ __forceinline__ void fence_async_smem() { asm volatile("fence.proxy.async.shared::cta;\n" ::: "memory"); }
__device__ __forceinline__ void bar_sync(int id, int n) { asm volatile("bar.sync %0, %1;" ::"r"(id), "r"(n) : "memory"); }
__device__ __forceinline__ void bar_arrive(int id, int n) { asm volatile("bar.arrive %0, %1;" ::"r"(id), "r"(n) : "memory"); }
__device__ __forceinline__ uint64_t make_desc(uint32_t addr, uint32_t lbo, uint32_t sbo, uint32_t swz) {
  return (uint64_t)((addr & 0x3FFFF) >> 4) | ((uint64_t)((lbo & 0x3FFFF) >> 4) << 16) | ((uint64_t)((sbo & 0x3FFFF) >> 4) << 32) | ((uint64_t)swz << 62);
}
__device__ __forceinline__ void mbar_init(uint32_t bar, int cnt) { asm volatile("mbarrier.init.shared::cta.b64 [%0], %1;" ::"r"(bar), "r"(cnt) : "memory"); }
__device__ __forceinline__ void mbar_expect_tx(uint32_t bar, uint32_t bytes) {
  asm volatile("mbarrier.arrive.expect_tx.shared::cta.b64 _, [%0], %1;" ::"r"(bar), "r"(bytes) : "memory");
}
__device__ __forceinline__ void mbar_arrive(uint32_t bar) { asm volatile("mbarrier.arrive.shared::cta.b64 _, [%0];" ::"r"(bar) : "memory"); }
__device__ __forceinline__ bool mbar_try(uint32_t bar, uint32_t parity) {
  uint32_t ok;
  asm volatile("{\n.reg .pred p;\nmbarrier.try_wait.parity.shared::cta.b64 p, [%1], %2;\nselp.u32 %0, 1, 0, p;\n}" : "=r"(ok) : "r"(bar), "r"(parity) : "memory");
  return ok != 0;
}
__device__ __forceinline__ void mbar_wait(uint32_t bar, uint32_t parity) {
  for (int i = 0; i < (1 << 22); i++) if (mbar_try(bar, parity)) return;
}
__device__ __forceinline__ void tma_load_2d(uint32_t dst, const CUtensorMap* tm, int c0, int c1, uint32_t bar) {
  asm volatile("cp.async.bulk.tensor.2d.shared::cluster.global.mbarrier::complete_tx::bytes [%0], [%1, {%3, %4}], [%2];"
               ::"r"(dst), "l"(tm), "r"(bar), "r"(c0), "r"(c1) : "memory");
}
__device__ __forceinline__ void tma_load_2d_mc(uint32_t dst, const CUtensorMap* tm, int c0, int c1, uint32_t bar, uint16_t mask) {
  asm volatile("cp.async.bulk.tensor.2d.shared::cluster.global.mbarrier::complete_tx::bytes.multicast::cluster [%0], [%1, {%3, %4}], [%2], %5;"
               ::"r"(dst), "l"(tm), "r"(bar), "r"(c0), "r"(c1), "h"(mask) : "memory");
}
__device__ __forceinline__ uint32_t pack_bf16(float lo, float hi) {
  uint32_t r; asm("cvt.rn.bf16x2.f32 %0, %1, %2;" : "=r"(r) : "f"(hi), "f"(lo)); return r;
}
__device__ __forceinline__ float bf_lo(uint32_t w) { return __uint_as_float(w << 16); }
__device__ __forceinline__ float bf_hi(uint32_t w) { return __uint_as_float(w & 0xffff0000u); }
__device__ __forceinline__ float rbf(float x) { return __bfloat162float(__float2bfloat16_rn(x)); }
__device__ __forceinline__ uint32_t prmt(uint32_t a, uint32_t b, uint32_t sel) { uint32_t r; asm("prmt.b32 %0, %1, %2, %3;" : "=r"(r) : "r"(a), "r"(b), "r"(sel)); return r; }
__device__ __forceinline__ uint4 ldg_nc_v4(const void* p) {
  uint4 v; asm volatile("ld.global.nc.L1::no_allocate.v4.u32 {%0,%1,%2,%3}, [%4];" : "=r"(v.x), "=r"(v.y), "=r"(v.z), "=r"(v.w) : "l"(p)); return v;
}
__device__ __forceinline__ void sts_v4(uint32_t a, uint4 v) { asm volatile("st.shared.v4.u32 [%0], {%1,%2,%3,%4};" ::"r"(a), "r"(v.x), "r"(v.y), "r"(v.z), "r"(v.w) : "memory"); }
__device__ __forceinline__ uint4 lds_v4(uint32_t a) { uint4 v; asm volatile("ld.shared.v4.u32 {%0,%1,%2,%3}, [%4];" : "=r"(v.x), "=r"(v.y), "=r"(v.z), "=r"(v.w) : "r"(a) : "memory"); return v; }
__device__ __forceinline__ uint32_t lds_u32(uint32_t a) { uint32_t v; asm volatile("ld.shared.u32 %0, [%1];" : "=r"(v) : "r"(a) : "memory"); return v; }
__device__ __forceinline__ void sts_u32(uint32_t a, uint32_t v) { asm volatile("st.shared.u32 [%0], %1;" ::"r"(a), "r"(v) : "memory"); }

template<int OFF, int NT> __device__ __forceinline__ void wg_rs_n8(float (&d)[NT], uint32_t a0, uint32_t a1, uint32_t a2, uint32_t a3, uint64_t db, int sd) {
  asm volatile("{\n.reg .pred p;\nsetp.ne.b32 p, %9, 0;\n"
    "wgmma.mma_async.sync.aligned.m64n8k16.f32.bf16.bf16 {%0, %1, %2, %3}, {%4, %5, %6, %7}, %8, p, 1, 1, 0;\n}\n"
    : "+f"(d[OFF + 0]), "+f"(d[OFF + 1]), "+f"(d[OFF + 2]), "+f"(d[OFF + 3]) : "r"(a0), "r"(a1), "r"(a2), "r"(a3), "l"(db), "r"(sd));
}
template<int OFF, int NT> __device__ __forceinline__ void wg_rs_n16(float (&d)[NT], uint32_t a0, uint32_t a1, uint32_t a2, uint32_t a3, uint64_t db, int sd) {
  asm volatile("{\n.reg .pred p;\nsetp.ne.b32 p, %13, 0;\n"
    "wgmma.mma_async.sync.aligned.m64n16k16.f32.bf16.bf16 {%0, %1, %2, %3, %4, %5, %6, %7}, {%8, %9, %10, %11}, %12, p, 1, 1, 0;\n}\n"
    : "+f"(d[OFF + 0]), "+f"(d[OFF + 1]), "+f"(d[OFF + 2]), "+f"(d[OFF + 3]), "+f"(d[OFF + 4]), "+f"(d[OFF + 5]), "+f"(d[OFF + 6]), "+f"(d[OFF + 7]) : "r"(a0), "r"(a1), "r"(a2), "r"(a3), "l"(db), "r"(sd));
}
template<int OFF, int NT> __device__ __forceinline__ void wg_rs_n24(float (&d)[NT], uint32_t a0, uint32_t a1, uint32_t a2, uint32_t a3, uint64_t db, int sd) {
  asm volatile("{\n.reg .pred p;\nsetp.ne.b32 p, %17, 0;\n"
    "wgmma.mma_async.sync.aligned.m64n24k16.f32.bf16.bf16 {%0, %1, %2, %3, %4, %5, %6, %7, %8, %9, %10, %11}, {%12, %13, %14, %15}, %16, p, 1, 1, 0;\n}\n"
    : "+f"(d[OFF + 0]), "+f"(d[OFF + 1]), "+f"(d[OFF + 2]), "+f"(d[OFF + 3]), "+f"(d[OFF + 4]), "+f"(d[OFF + 5]), "+f"(d[OFF + 6]), "+f"(d[OFF + 7]), "+f"(d[OFF + 8]), "+f"(d[OFF + 9]), "+f"(d[OFF + 10]), "+f"(d[OFF + 11]) : "r"(a0), "r"(a1), "r"(a2), "r"(a3), "l"(db), "r"(sd));
}
template<int OFF, int NT> __device__ __forceinline__ void wg_rs_n32(float (&d)[NT], uint32_t a0, uint32_t a1, uint32_t a2, uint32_t a3, uint64_t db, int sd) {
  asm volatile("{\n.reg .pred p;\nsetp.ne.b32 p, %21, 0;\n"
    "wgmma.mma_async.sync.aligned.m64n32k16.f32.bf16.bf16 {%0, %1, %2, %3, %4, %5, %6, %7, %8, %9, %10, %11, %12, %13, %14, %15}, {%16, %17, %18, %19}, %20, p, 1, 1, 0;\n}\n"
    : "+f"(d[OFF + 0]), "+f"(d[OFF + 1]), "+f"(d[OFF + 2]), "+f"(d[OFF + 3]), "+f"(d[OFF + 4]), "+f"(d[OFF + 5]), "+f"(d[OFF + 6]), "+f"(d[OFF + 7]), "+f"(d[OFF + 8]), "+f"(d[OFF + 9]), "+f"(d[OFF + 10]), "+f"(d[OFF + 11]), "+f"(d[OFF + 12]), "+f"(d[OFF + 13]), "+f"(d[OFF + 14]), "+f"(d[OFF + 15]) : "r"(a0), "r"(a1), "r"(a2), "r"(a3), "l"(db), "r"(sd));
}
template<int OFF, int NT> __device__ __forceinline__ void wg_rs_n40(float (&d)[NT], uint32_t a0, uint32_t a1, uint32_t a2, uint32_t a3, uint64_t db, int sd) {
  asm volatile("{\n.reg .pred p;\nsetp.ne.b32 p, %25, 0;\n"
    "wgmma.mma_async.sync.aligned.m64n40k16.f32.bf16.bf16 {%0, %1, %2, %3, %4, %5, %6, %7, %8, %9, %10, %11, %12, %13, %14, %15, %16, %17, %18, %19}, {%20, %21, %22, %23}, %24, p, 1, 1, 0;\n}\n"
    : "+f"(d[OFF + 0]), "+f"(d[OFF + 1]), "+f"(d[OFF + 2]), "+f"(d[OFF + 3]), "+f"(d[OFF + 4]), "+f"(d[OFF + 5]), "+f"(d[OFF + 6]), "+f"(d[OFF + 7]), "+f"(d[OFF + 8]), "+f"(d[OFF + 9]), "+f"(d[OFF + 10]), "+f"(d[OFF + 11]), "+f"(d[OFF + 12]), "+f"(d[OFF + 13]), "+f"(d[OFF + 14]), "+f"(d[OFF + 15]), "+f"(d[OFF + 16]), "+f"(d[OFF + 17]), "+f"(d[OFF + 18]), "+f"(d[OFF + 19]) : "r"(a0), "r"(a1), "r"(a2), "r"(a3), "l"(db), "r"(sd));
}
template<int OFF, int NT> __device__ __forceinline__ void wg_rs_n48(float (&d)[NT], uint32_t a0, uint32_t a1, uint32_t a2, uint32_t a3, uint64_t db, int sd) {
  asm volatile("{\n.reg .pred p;\nsetp.ne.b32 p, %29, 0;\n"
    "wgmma.mma_async.sync.aligned.m64n48k16.f32.bf16.bf16 {%0, %1, %2, %3, %4, %5, %6, %7, %8, %9, %10, %11, %12, %13, %14, %15, %16, %17, %18, %19, %20, %21, %22, %23}, {%24, %25, %26, %27}, %28, p, 1, 1, 0;\n}\n"
    : "+f"(d[OFF + 0]), "+f"(d[OFF + 1]), "+f"(d[OFF + 2]), "+f"(d[OFF + 3]), "+f"(d[OFF + 4]), "+f"(d[OFF + 5]), "+f"(d[OFF + 6]), "+f"(d[OFF + 7]), "+f"(d[OFF + 8]), "+f"(d[OFF + 9]), "+f"(d[OFF + 10]), "+f"(d[OFF + 11]), "+f"(d[OFF + 12]), "+f"(d[OFF + 13]), "+f"(d[OFF + 14]), "+f"(d[OFF + 15]), "+f"(d[OFF + 16]), "+f"(d[OFF + 17]), "+f"(d[OFF + 18]), "+f"(d[OFF + 19]), "+f"(d[OFF + 20]), "+f"(d[OFF + 21]), "+f"(d[OFF + 22]), "+f"(d[OFF + 23]) : "r"(a0), "r"(a1), "r"(a2), "r"(a3), "l"(db), "r"(sd));
}
template<int OFF, int NT> __device__ __forceinline__ void wg_rs_n56(float (&d)[NT], uint32_t a0, uint32_t a1, uint32_t a2, uint32_t a3, uint64_t db, int sd) {
  asm volatile("{\n.reg .pred p;\nsetp.ne.b32 p, %33, 0;\n"
    "wgmma.mma_async.sync.aligned.m64n56k16.f32.bf16.bf16 {%0, %1, %2, %3, %4, %5, %6, %7, %8, %9, %10, %11, %12, %13, %14, %15, %16, %17, %18, %19, %20, %21, %22, %23, %24, %25, %26, %27}, {%28, %29, %30, %31}, %32, p, 1, 1, 0;\n}\n"
    : "+f"(d[OFF + 0]), "+f"(d[OFF + 1]), "+f"(d[OFF + 2]), "+f"(d[OFF + 3]), "+f"(d[OFF + 4]), "+f"(d[OFF + 5]), "+f"(d[OFF + 6]), "+f"(d[OFF + 7]), "+f"(d[OFF + 8]), "+f"(d[OFF + 9]), "+f"(d[OFF + 10]), "+f"(d[OFF + 11]), "+f"(d[OFF + 12]), "+f"(d[OFF + 13]), "+f"(d[OFF + 14]), "+f"(d[OFF + 15]), "+f"(d[OFF + 16]), "+f"(d[OFF + 17]), "+f"(d[OFF + 18]), "+f"(d[OFF + 19]), "+f"(d[OFF + 20]), "+f"(d[OFF + 21]), "+f"(d[OFF + 22]), "+f"(d[OFF + 23]), "+f"(d[OFF + 24]), "+f"(d[OFF + 25]), "+f"(d[OFF + 26]), "+f"(d[OFF + 27]) : "r"(a0), "r"(a1), "r"(a2), "r"(a3), "l"(db), "r"(sd));
}
template<int OFF, int NT> __device__ __forceinline__ void wg_rs_n64(float (&d)[NT], uint32_t a0, uint32_t a1, uint32_t a2, uint32_t a3, uint64_t db, int sd) {
  asm volatile("{\n.reg .pred p;\nsetp.ne.b32 p, %37, 0;\n"
    "wgmma.mma_async.sync.aligned.m64n64k16.f32.bf16.bf16 {%0, %1, %2, %3, %4, %5, %6, %7, %8, %9, %10, %11, %12, %13, %14, %15, %16, %17, %18, %19, %20, %21, %22, %23, %24, %25, %26, %27, %28, %29, %30, %31}, {%32, %33, %34, %35}, %36, p, 1, 1, 0;\n}\n"
    : "+f"(d[OFF + 0]), "+f"(d[OFF + 1]), "+f"(d[OFF + 2]), "+f"(d[OFF + 3]), "+f"(d[OFF + 4]), "+f"(d[OFF + 5]), "+f"(d[OFF + 6]), "+f"(d[OFF + 7]), "+f"(d[OFF + 8]), "+f"(d[OFF + 9]), "+f"(d[OFF + 10]), "+f"(d[OFF + 11]), "+f"(d[OFF + 12]), "+f"(d[OFF + 13]), "+f"(d[OFF + 14]), "+f"(d[OFF + 15]), "+f"(d[OFF + 16]), "+f"(d[OFF + 17]), "+f"(d[OFF + 18]), "+f"(d[OFF + 19]), "+f"(d[OFF + 20]), "+f"(d[OFF + 21]), "+f"(d[OFF + 22]), "+f"(d[OFF + 23]), "+f"(d[OFF + 24]), "+f"(d[OFF + 25]), "+f"(d[OFF + 26]), "+f"(d[OFF + 27]), "+f"(d[OFF + 28]), "+f"(d[OFF + 29]), "+f"(d[OFF + 30]), "+f"(d[OFF + 31]) : "r"(a0), "r"(a1), "r"(a2), "r"(a3), "l"(db), "r"(sd));
}
template<int OFF, int NT> __device__ __forceinline__ void wg_rs_n8_tb(float (&d)[NT], uint32_t a0, uint32_t a1, uint32_t a2, uint32_t a3, uint64_t db, int sd) {
  asm volatile("{\n.reg .pred p;\nsetp.ne.b32 p, %9, 0;\n"
    "wgmma.mma_async.sync.aligned.m64n8k16.f32.bf16.bf16 {%0, %1, %2, %3}, {%4, %5, %6, %7}, %8, p, 1, 1, 1;\n}\n"
    : "+f"(d[OFF + 0]), "+f"(d[OFF + 1]), "+f"(d[OFF + 2]), "+f"(d[OFF + 3]) : "r"(a0), "r"(a1), "r"(a2), "r"(a3), "l"(db), "r"(sd));
}
template<int OFF, int NT> __device__ __forceinline__ void wg_rs_n16_tb(float (&d)[NT], uint32_t a0, uint32_t a1, uint32_t a2, uint32_t a3, uint64_t db, int sd) {
  asm volatile("{\n.reg .pred p;\nsetp.ne.b32 p, %13, 0;\n"
    "wgmma.mma_async.sync.aligned.m64n16k16.f32.bf16.bf16 {%0, %1, %2, %3, %4, %5, %6, %7}, {%8, %9, %10, %11}, %12, p, 1, 1, 1;\n}\n"
    : "+f"(d[OFF + 0]), "+f"(d[OFF + 1]), "+f"(d[OFF + 2]), "+f"(d[OFF + 3]), "+f"(d[OFF + 4]), "+f"(d[OFF + 5]), "+f"(d[OFF + 6]), "+f"(d[OFF + 7]) : "r"(a0), "r"(a1), "r"(a2), "r"(a3), "l"(db), "r"(sd));
}
template<int OFF, int NT> __device__ __forceinline__ void wg_ss_n16_ta_tb(float (&d)[NT], uint64_t da, uint64_t db, int sd) {
  asm volatile("{\n.reg .pred p;\nsetp.ne.b32 p, %10, 0;\n"
    "wgmma.mma_async.sync.aligned.m64n16k16.f32.bf16.bf16 {%0, %1, %2, %3, %4, %5, %6, %7}, %8, %9, p, 1, 1, 1, 1;\n}\n"
    : "+f"(d[OFF + 0]), "+f"(d[OFF + 1]), "+f"(d[OFF + 2]), "+f"(d[OFF + 3]), "+f"(d[OFF + 4]), "+f"(d[OFF + 5]), "+f"(d[OFF + 6]), "+f"(d[OFF + 7]) : "l"(da), "l"(db), "r"(sd));
}
template<int OFF, int NT> __device__ __forceinline__ void wg_ss_n64_ta(float (&d)[NT], uint64_t da, uint64_t db, int sd) {
  asm volatile("{\n.reg .pred p;\nsetp.ne.b32 p, %34, 0;\n"
    "wgmma.mma_async.sync.aligned.m64n64k16.f32.bf16.bf16 {%0, %1, %2, %3, %4, %5, %6, %7, %8, %9, %10, %11, %12, %13, %14, %15, %16, %17, %18, %19, %20, %21, %22, %23, %24, %25, %26, %27, %28, %29, %30, %31}, %32, %33, p, 1, 1, 1, 0;\n}\n"
    : "+f"(d[OFF + 0]), "+f"(d[OFF + 1]), "+f"(d[OFF + 2]), "+f"(d[OFF + 3]), "+f"(d[OFF + 4]), "+f"(d[OFF + 5]), "+f"(d[OFF + 6]), "+f"(d[OFF + 7]), "+f"(d[OFF + 8]), "+f"(d[OFF + 9]), "+f"(d[OFF + 10]), "+f"(d[OFF + 11]), "+f"(d[OFF + 12]), "+f"(d[OFF + 13]), "+f"(d[OFF + 14]), "+f"(d[OFF + 15]), "+f"(d[OFF + 16]), "+f"(d[OFF + 17]), "+f"(d[OFF + 18]), "+f"(d[OFF + 19]), "+f"(d[OFF + 20]), "+f"(d[OFF + 21]), "+f"(d[OFF + 22]), "+f"(d[OFF + 23]), "+f"(d[OFF + 24]), "+f"(d[OFF + 25]), "+f"(d[OFF + 26]), "+f"(d[OFF + 27]), "+f"(d[OFF + 28]), "+f"(d[OFF + 29]), "+f"(d[OFF + 30]), "+f"(d[OFF + 31]) : "l"(da), "l"(db), "r"(sd));
}
template<int OFF, int NT> __device__ __forceinline__ void wg_ss_n8_ta(float (&d)[NT], uint64_t da, uint64_t db, int sd) {
  asm volatile("{\n.reg .pred p;\nsetp.ne.b32 p, %6, 0;\n"
    "wgmma.mma_async.sync.aligned.m64n8k16.f32.bf16.bf16 {%0, %1, %2, %3}, %4, %5, p, 1, 1, 1, 0;\n}\n"
    : "+f"(d[OFF + 0]), "+f"(d[OFF + 1]), "+f"(d[OFF + 2]), "+f"(d[OFF + 3]) : "l"(da), "l"(db), "r"(sd));
}
template<int OFF, int NT> __device__ __forceinline__ void wg_ss_n128_tb(float (&d)[NT], uint64_t da, uint64_t db, int sd) {
  asm volatile("{\n.reg .pred p;\nsetp.ne.b32 p, %66, 0;\n"
    "wgmma.mma_async.sync.aligned.m64n128k16.f32.bf16.bf16 {%0, %1, %2, %3, %4, %5, %6, %7, %8, %9, %10, %11, %12, %13, %14, %15, %16, %17, %18, %19, %20, %21, %22, %23, %24, %25, %26, %27, %28, %29, %30, %31, %32, %33, %34, %35, %36, %37, %38, %39, %40, %41, %42, %43, %44, %45, %46, %47, %48, %49, %50, %51, %52, %53, %54, %55, %56, %57, %58, %59, %60, %61, %62, %63}, %64, %65, p, 1, 1, 0, 1;\n}\n"
    : "+f"(d[OFF + 0]), "+f"(d[OFF + 1]), "+f"(d[OFF + 2]), "+f"(d[OFF + 3]), "+f"(d[OFF + 4]), "+f"(d[OFF + 5]), "+f"(d[OFF + 6]), "+f"(d[OFF + 7]), "+f"(d[OFF + 8]), "+f"(d[OFF + 9]), "+f"(d[OFF + 10]), "+f"(d[OFF + 11]), "+f"(d[OFF + 12]), "+f"(d[OFF + 13]), "+f"(d[OFF + 14]), "+f"(d[OFF + 15]), "+f"(d[OFF + 16]), "+f"(d[OFF + 17]), "+f"(d[OFF + 18]), "+f"(d[OFF + 19]), "+f"(d[OFF + 20]), "+f"(d[OFF + 21]), "+f"(d[OFF + 22]), "+f"(d[OFF + 23]), "+f"(d[OFF + 24]), "+f"(d[OFF + 25]), "+f"(d[OFF + 26]), "+f"(d[OFF + 27]), "+f"(d[OFF + 28]), "+f"(d[OFF + 29]), "+f"(d[OFF + 30]), "+f"(d[OFF + 31]), "+f"(d[OFF + 32]), "+f"(d[OFF + 33]), "+f"(d[OFF + 34]), "+f"(d[OFF + 35]), "+f"(d[OFF + 36]), "+f"(d[OFF + 37]), "+f"(d[OFF + 38]), "+f"(d[OFF + 39]), "+f"(d[OFF + 40]), "+f"(d[OFF + 41]), "+f"(d[OFF + 42]), "+f"(d[OFF + 43]), "+f"(d[OFF + 44]), "+f"(d[OFF + 45]), "+f"(d[OFF + 46]), "+f"(d[OFF + 47]), "+f"(d[OFF + 48]), "+f"(d[OFF + 49]), "+f"(d[OFF + 50]), "+f"(d[OFF + 51]), "+f"(d[OFF + 52]), "+f"(d[OFF + 53]), "+f"(d[OFF + 54]), "+f"(d[OFF + 55]), "+f"(d[OFF + 56]), "+f"(d[OFF + 57]), "+f"(d[OFF + 58]), "+f"(d[OFF + 59]), "+f"(d[OFF + 60]), "+f"(d[OFF + 61]), "+f"(d[OFF + 62]), "+f"(d[OFF + 63]) : "l"(da), "l"(db), "r"(sd));
}
template<int OFF, int NT> __device__ __forceinline__ void wg_ss_n8_ta_tb(float (&d)[NT], uint64_t da, uint64_t db, int sd) {
  asm volatile("{\n.reg .pred p;\nsetp.ne.b32 p, %6, 0;\n"
    "wgmma.mma_async.sync.aligned.m64n8k16.f32.bf16.bf16 {%0, %1, %2, %3}, %4, %5, p, 1, 1, 1, 1;\n}\n"
    : "+f"(d[OFF + 0]), "+f"(d[OFF + 1]), "+f"(d[OFF + 2]), "+f"(d[OFF + 3]) : "l"(da), "l"(db), "r"(sd));
}
template<int OFF, int NT> __device__ __forceinline__ void wg_ss_n32_ta(float (&d)[NT], uint64_t da, uint64_t db, int sd) {
  asm volatile("{\n.reg .pred p;\nsetp.ne.b32 p, %18, 0;\n"
    "wgmma.mma_async.sync.aligned.m64n32k16.f32.bf16.bf16 {%0, %1, %2, %3, %4, %5, %6, %7, %8, %9, %10, %11, %12, %13, %14, %15}, %16, %17, p, 1, 1, 1, 0;\n}\n"
    : "+f"(d[OFF + 0]), "+f"(d[OFF + 1]), "+f"(d[OFF + 2]), "+f"(d[OFF + 3]), "+f"(d[OFF + 4]), "+f"(d[OFF + 5]), "+f"(d[OFF + 6]), "+f"(d[OFF + 7]), "+f"(d[OFF + 8]), "+f"(d[OFF + 9]), "+f"(d[OFF + 10]), "+f"(d[OFF + 11]), "+f"(d[OFF + 12]), "+f"(d[OFF + 13]), "+f"(d[OFF + 14]), "+f"(d[OFF + 15]) : "l"(da), "l"(db), "r"(sd));
}

__device__ float g_gate[SEQ];
__device__ bf16 g_ox[SEQ * HD];

__device__ bf16 g_kvT[DM * SEQ];
__device__ unsigned g_kvT_ready;
__constant__ int g_one = 1;
__device__ bf16 g_y2T[DM * SEQ];

#define KB_BG_ 96
constexpr int KB_BG = KB_BG_;
constexpr int KB_UL = 81 * 16;
constexpr int KB_U = 4 * KB_UL;
constexpr int KB_K = 2080 * 4;
constexpr int KB_BUF = KB_U + KB_K;
constexpr int KB_SC = 65 * 36 * 4;
constexpr int KB_WG = 2 * KB_BUF + 2 * KB_SC;
constexpr int KB_SMEM = 4 * KB_WG;
static_assert(KB_WG % 16 == 0 && KB_SMEM >= 32768 && KB_SMEM < 200000, "kb smem");

template <int EPS> __device__ __forceinline__ void kb_mma(float (&acc)[32], const uint32_t (&r)[8], uint64_t db0) {
  constexpr int GI = 2 * (EPS / 8);
  const uint64_t d0 = db0 + 2 * EPS, d1 = db0 + 2 * EPS + ((2 * KB_UL) >> 4);
  constexpr int sd = (EPS == 0) ? 0 : 1;
  if constexpr (GI == 0) { wg_rs_n64<0>(acc, r[0], r[1], r[2], r[3], d0, sd); wg_rs_n64<0>(acc, r[4], r[5], r[6], r[7], d1, 1); }
  if constexpr (GI == 1) { wg_rs_n56<0>(acc, r[0], r[1], r[2], r[3], d0, 1); wg_rs_n56<0>(acc, r[4], r[5], r[6], r[7], d1, 1); }
  if constexpr (GI == 2) { wg_rs_n48<0>(acc, r[0], r[1], r[2], r[3], d0, 1); wg_rs_n48<0>(acc, r[4], r[5], r[6], r[7], d1, 1); }
  if constexpr (GI == 3) { wg_rs_n40<0>(acc, r[0], r[1], r[2], r[3], d0, 1); wg_rs_n40<0>(acc, r[4], r[5], r[6], r[7], d1, 1); }
  if constexpr (GI == 4) { wg_rs_n32<0>(acc, r[0], r[1], r[2], r[3], d0, 1); wg_rs_n32<0>(acc, r[4], r[5], r[6], r[7], d1, 1); }
  if constexpr (GI == 5) { wg_rs_n24<0>(acc, r[0], r[1], r[2], r[3], d0, 1); wg_rs_n24<0>(acc, r[4], r[5], r[6], r[7], d1, 1); }
  if constexpr (GI == 6) { wg_rs_n16<0>(acc, r[0], r[1], r[2], r[3], d0, 1); wg_rs_n16<0>(acc, r[4], r[5], r[6], r[7], d1, 1); }
  if constexpr (GI == 7) { wg_rs_n8<0>(acc, r[0], r[1], r[2], r[3], d0, 1); wg_rs_n8<0>(acc, r[4], r[5], r[6], r[7], d1, 1); }
}
template <int EPS> __device__ __forceinline__ void kb_lda(uint32_t (&r)[8], uint32_t ka) {
  r[0] = lds_u32(ka + (EPS * 32) * 4); r[1] = lds_u32(ka + (EPS * 32 + 4) * 4); r[2] = lds_u32(ka + (EPS * 32 - 4) * 4);
  r[4] = lds_u32(ka + (EPS * 32 - 8) * 4); r[6] = lds_u32(ka + (EPS * 32 - 12) * 4);
  r[3] = lds_u32(ka + (EPS * 32) * 4); r[5] = lds_u32(ka + (EPS * 32 - 4) * 4); r[7] = lds_u32(ka + (EPS * 32 - 8) * 4);
}
template <int E0> __device__ __forceinline__ void kb_steps(float (&acc)[32], uint32_t (&r0)[2][8], uint32_t (&r1)[2][8], uint32_t ka, uint64_t db0) {
  if constexpr (E0 < 32) {
    wg_fence();
    kb_mma<E0>(acc, r0[0], db0); kb_mma<E0 + 1>(acc, r0[1], db0);
    wg_commit();
    if constexpr (E0 + 2 < 32) {
      wg_wait<1>();
      kb_lda<E0 + 2>(r1[0], ka); kb_lda<E0 + 3>(r1[1], ka);
    }
    kb_steps<E0 + 2>(acc, r1, r0, ka, db0);
  }
}
template <int E0> __device__ __forceinline__ void kb_steps_simple(float (&acc)[32], uint32_t ka, uint64_t db0) {
  if constexpr (E0 < 32) {
    uint32_t r[2][8];
    kb_lda<E0>(r[0], ka); kb_lda<E0 + 1>(r[1], ka);
    wg_fence();
    kb_mma<E0>(acc, r[0], db0); kb_mma<E0 + 1>(acc, r[1], db0);
    wg_commit();
    wg_wait<0>();
    kb_steps_simple<E0 + 2>(acc, ka, db0);
  }
}
__device__ __forceinline__ uint32_t bmul2(uint32_t a, uint32_t b) { uint32_t r; asm("mul.rn.bf16x2 %0, %1, %2;" : "=r"(r) : "r"(a), "r"(b)); return r; }
__device__ __forceinline__ uint32_t badd2(uint32_t a, uint32_t b) { uint32_t r; asm("add.rn.bf16x2 %0, %1, %2;" : "=r"(r) : "r"(a), "r"(b)); return r; }
__device__ __forceinline__ void cp_async16(uint32_t dst, const void* src) { asm volatile("cp.async.cg.shared.global [%0], [%1], 16;" ::"r"(dst), "l"(src) : "memory"); }

template <bool PIPE> __device__ __forceinline__ void conv_channels(uint32_t wb, int t128, int barid, int ch0, int chs, int nch, const bf16* __restrict__ ssm_k,
                                              const bf16* __restrict__ ssm_D) {
  const int lane = t128 & 31, wq = t128 >> 5, g = lane >> 2, tq = lane & 3;
  const uint32_t sc = wb + 2 * KB_BUF;
  if (t128 >= 96 && t128 < 105) sts_v4(sc + KB_SC + (t128 - 96) * 16, make_uint4(0, 0, 0, 0));
  sts_v4(wb + (t128 >> 6) * KB_BUF + ((t128 >> 4) & 3) * KB_UL + (64 + (t128 & 15)) * 16, make_uint4(0, 0, 0, 0));
  if (t128 >= 64 && t128 < 80) sts_v4(wb + ((t128 >> 3) & 1) * KB_BUF + KB_U + ((t128 >> 2) & 1) * 4160 + (t128 & 3) * 16, make_uint4(0, 0, 0, 0));
  uint4 kw[2]; uint32_t pw[2];
  auto fetch = [&](int i) {
    const int ch = ch0 + chs * i;
    const uint32_t ub = wb + (i & 1) * KB_BUF;
#pragma unroll
    for (int r = 0; r < 2; r++) {
      const int m = r * 128 + t128;
      cp_async16(ub + (m & 3) * KB_UL + (63 - (m >> 2)) * 16, g_kvT + (size_t)ch * SEQ + m * 8);
      const bf16* src = ssm_k + (size_t)ch * SEQ + m * 8;
      kw[r] = ldg_nc_v4(src);
      pw[r] = (m > 0) ? *reinterpret_cast<const uint32_t*>(src - 2) : 0u;
    }
  };
  auto stash = [&](int i) {
    const uint32_t kb = wb + (i & 1) * KB_BUF + KB_U;
#pragma unroll
    for (int r = 0; r < 2; r++) {
      const uint32_t ka = kb + (16 + (r * 128 + t128) * 4) * 4;
      sts_v4(ka, make_uint4(prmt(kw[r].x, pw[r], 0x7610u), prmt(kw[r].y, kw[r].x, 0x7610u), prmt(kw[r].z, kw[r].y, 0x7610u), prmt(kw[r].w, kw[r].z, 0x7610u)));
      sts_v4(ka + 4160, make_uint4(prmt(kw[r].x, 0, 0x1032u), prmt(kw[r].y, 0, 0x1032u), prmt(kw[r].z, 0, 0x1032u), prmt(kw[r].w, 0, 0x1032u)));
    }
    asm volatile("cp.async.wait_all;" ::: "memory");
    fence_async_smem();
    bar_sync(barid, 128);
  };
  fetch(0);
  stash(0);
#pragma unroll 1
  for (int i = 0; i < nch; i++) {
    const int ch = ch0 + chs * i;
    const uint32_t ub = wb + (i & 1) * KB_BUF;
    if (i + 1 < nch) fetch(i + 1);
    const uint32_t D2 = 0x10001u * (uint32_t)__bfloat16_as_ushort(ssm_D[ch]);
    const int i0 = 16 * wq + g - 2 * tq;
    const uint32_t ka = ub + KB_U + (g & 1) * 4160 + ((i0 >> 1) + 16) * 4;
    const uint64_t db0 = make_desc(ub, KB_UL, 128, 0);
    float acc[32];
    if constexpr (PIPE) {
      uint32_t ra[2][8], rb[2][8];
      kb_lda<0>(ra[0], ka); kb_lda<1>(ra[1], ka);
      kb_steps<0>(acc, ra, rb, ka, db0);
    } else {
      kb_steps_simple<0>(acc, ka, db0);
    }
    wg_wait<0>(); fence_regs(acc);
    {
      const uint32_t pl = sc + (wq >> 1) * (KB_SC + 144) + ((wq & 1) * 16 + g) * 4;
#pragma unroll
      for (int j = 0; j < 8; j++)
#pragma unroll
        for (int e = 0; e < 4; e++) {
          const int a = 63 - (8 * j + 2 * tq + (e & 1));
          asm volatile("st.shared.f32 [%0], %1;" ::"r"(pl + (a * 36 + (e >> 1) * 8) * 4), "f"(acc[4 * j + e]) : "memory");
        }
    }
    bar_sync(barid, 128);
    {
      const int a = t128 >> 1, hb = t128 & 1;
      const uint32_t p0 = sc + (a * 36 + hb * 16) * 4;
#pragma unroll
      for (int u = 0; u < 2; u++) {
        const uint4 kv = lds_v4(ub + (2 * hb + u) * KB_UL + (63 - a) * 16);
        const uint32_t kvw[4] = {kv.x, kv.y, kv.z, kv.w};
        uint32_t o[4];
#pragma unroll
        for (int v4 = 0; v4 < 2; v4++) {
          const uint4 x = lds_v4(p0 + (u * 8 + v4 * 4) * 4), y = lds_v4(p0 + KB_SC + (u * 8 + v4 * 4) * 4);
          const uint32_t y01 = pack_bf16(__uint_as_float(x.x) + __uint_as_float(y.x), __uint_as_float(x.y) + __uint_as_float(y.y));
          const uint32_t y23 = pack_bf16(__uint_as_float(x.z) + __uint_as_float(y.z), __uint_as_float(x.w) + __uint_as_float(y.w));
          o[2 * v4] = badd2(y01, bmul2(kvw[2 * v4], D2));
          o[2 * v4 + 1] = badd2(y23, bmul2(kvw[2 * v4 + 1], D2));
        }
        *reinterpret_cast<uint4*>(g_y2T + (size_t)ch * SEQ + t128 * 16 + u * 8) = make_uint4(o[0], o[1], o[2], o[3]);
      }
    }
    if (i + 1 < nch) stash(i + 1);
  }
}

__global__ void __cluster_dims__(2, 1, 1) __launch_bounds__(512, 1)
kb_conv(const bf16* __restrict__ q, const bf16* __restrict__ gate_w, const bf16* __restrict__ k, const bf16* __restrict__ v, const bf16* __restrict__ shift_k,
        const bf16* __restrict__ ssm_k, const bf16* __restrict__ ssm_D) {
  extern __shared__ __align__(1024) uint8_t smem[];
  const uint32_t sb = smem_u32(smem);
  const int tid = threadIdx.x, lane = tid & 31, warp = tid >> 5;
  const int c0 = blockIdx.x * 256;
#define KB_SLEEP 0
#pragma unroll 1
  for (int i = 0; i < KB_SLEEP; i++) __nanosleep(1000);
  {
    const int d0 = c0 + lane * 8;
    uint32_t sk[4][4];
#pragma unroll
    for (int p = 0; p < 4; p++) {
      const uint2 a = *reinterpret_cast<const uint2*>(shift_k + (d0 + 2 * p) * 4), b = *reinterpret_cast<const uint2*>(shift_k + (d0 + 2 * p + 1) * 4);
      sk[0][p] = prmt(a.x, b.x, 0x5410u); sk[1][p] = prmt(a.x, b.x, 0x7632u); sk[2][p] = prmt(a.y, b.y, 0x5410u); sk[3][p] = prmt(a.y, b.y, 0x7632u);
    }
    uint4 kr[7], vr[4];
    auto load = [&](int it) {
      const int t0 = it * 64 + warp * 4;
#pragma unroll
      for (int i = 0; i < 7; i++) { const int t = t0 - 3 + i; kr[i] = (t >= 0) ? ldg_nc_v4(k + (size_t)t * DM + d0) : make_uint4(0, 0, 0, 0); }
#pragma unroll
      for (int i = 0; i < 4; i++) vr[i] = ldg_nc_v4(v + (size_t)(t0 + i) * DM + d0);
    };
    load(0);
#pragma unroll 1
    for (int it = 0; it < 32; it++) {
      uint32_t row[4][4];
#pragma unroll
      for (int i = 0; i < 4; i++)
#pragma unroll
        for (int p = 0; p < 4; p++) {
          uint32_t a = bmul2(reinterpret_cast<const uint32_t*>(&kr[i])[p], sk[3][p]);
          a = badd2(a, bmul2(reinterpret_cast<const uint32_t*>(&kr[i + 1])[p], sk[2][p]));
          a = badd2(a, bmul2(reinterpret_cast<const uint32_t*>(&kr[i + 2])[p], sk[1][p]));
          a = badd2(a, bmul2(reinterpret_cast<const uint32_t*>(&kr[i + 3])[p], sk[0][p]));
          row[i][p] = bmul2(a, reinterpret_cast<const uint32_t*>(&vr[i])[p]);
        }
      if (it + 1 < 32) load(it + 1);
      const uint32_t ta = sb + (lane * 8) * 128 + ((warp ^ (lane & 15)) << 3);
#pragma unroll
      for (int c = 0; c < 8; c++) {
        const uint32_t sel = (c & 1) ? 0x7632u : 0x5410u;
        asm volatile("st.shared.v2.u32 [%0], {%1,%2};" ::"r"(ta + c * 128), "r"(prmt(row[0][c >> 1], row[1][c >> 1], sel)),
                     "r"(prmt(row[2][c >> 1], row[3][c >> 1], sel)) : "memory");
      }
      __syncthreads();
#pragma unroll
      for (int i = 0; i < 4; i++) {
        const int idx = i * 512 + tid, ch = idx >> 3, pc = idx & 7, x = (ch >> 3) & 15;
        uint4 w = lds_v4(sb + ch * 128 + (((2 * pc) ^ (x & 14)) << 3));
        if (x & 1) w = make_uint4(w.z, w.w, w.x, w.y);
        *reinterpret_cast<uint4*>(g_kvT + (size_t)(c0 + ch) * SEQ + it * 64 + pc * 8) = w;
      }
      __syncthreads();
    }
  }
  __threadfence();
  __syncthreads();
  if (tid == 0) asm volatile("red.release.gpu.global.add.u32 [%0], 1;" ::"l"(&g_kvT_ready) : "memory");
  if (warp >= 12) {
    asm volatile("setmaxnreg.dec.sync.aligned.u32 40;\n");
    if (tid - 384 < 256 - KB_BG) asm volatile("cp.async.bulk.prefetch.L2.global [%0], %1;" ::"l"(ssm_k + (size_t)(c0 + KB_BG + tid - 384) * SEQ), "r"(4096) : "memory");
    asm volatile("cp.async.bulk.prefetch.L2.global [%0], %1;" ::"l"(q + (size_t)(blockIdx.x * 512 + (tid - 384) * 4) * DM), "r"(8192) : "memory");
#pragma unroll 1
    for (int t = blockIdx.x * 512 + (warp - 12) * 2 + (lane >> 4); t < blockIdx.x * 512 + 512; t += 8) {
      float s = 0.f;
#pragma unroll
      for (int hh = 0; hh < 2; hh++) {
        uint4 xv[4];
#pragma unroll
        for (int i = 0; i < 4; i++) xv[i] = ldg_nc_v4(q + (size_t)t * DM + (hh * 4 + i) * 128 + (lane & 15) * 8);
#pragma unroll
        for (int i = 0; i < 4; i++) {
          const uint4 gw = *reinterpret_cast<const uint4*>(gate_w + (hh * 4 + i) * 128 + (lane & 15) * 8);
#pragma unroll
          for (int c = 0; c < 4; c++) {
            const uint32_t pr = bmul2(reinterpret_cast<const uint32_t*>(&xv[i])[c], reinterpret_cast<const uint32_t*>(&gw)[c]);
            s += bf_lo(pr) + bf_hi(pr);
          }
        }
      }
#pragma unroll
      for (int o = 8; o > 0; o >>= 1) s += __shfl_xor_sync(0xffffffffu, s, o);
      if ((lane & 15) == 0) { const float z = rbf(s); g_gate[t] = rbf(1.f / (1.f + __expf(-z))); }
    }
    return;
  }
  asm volatile("setmaxnreg.inc.sync.aligned.u32 152;\n");
  conv_channels<true>(sb + (warp >> 2) * KB_WG, tid & 127, 1 + (warp >> 2), c0 + (warp >> 2), 3, KB_BG / 3, ssm_k, ssm_D);
}

constexpr uint32_t XW_MEM = 0, XW_PROBE = 65536, XW_O = 131072, XW_VX = 262144, XW_VM = 524288, XW_SLOT = 1u << 20;
__device__ uint4 g_xw[(4 << 20) / 16];
__device__ __align__(1024) uint4 g_sx[2][64][256];
constexpr int KR = 24;
constexpr int POLL_MAX = 200000;

constexpr uint32_t Q_WRES = 0, Q_XT = 65536, Q_STG = 98304;
constexpr uint32_t Q_MEMS = 131072, Q_LAND = Q_MEMS + 8192, Q_QEX = Q_LAND + 16384, Q_KEX = Q_QEX + 2048, Q_KXEX = Q_KEX + 2048, Q_QF = Q_KXEX + 8192, Q_KX = Q_QF + 2048,
                   Q_QX = Q_KX + 10240, Q_SMM = Q_QX + 8192, Q_SMX = Q_SMM + 2048, Q_VM = Q_SMX + 1024, Q_TAB = 196608;
static_assert(Q_VM + 1024 <= Q_TAB, "smem");
constexpr uint32_t V_WRES = 0, V_XT = 32768, V_STG = 98304, V_RED = 6144;
constexpr uint32_t V_MEMS = V_STG + 8192, V_VXEX = V_STG + 4 * 16384 + 7168, V_VXS = V_STG + 2 * 16384 + 8192, V_PS = V_STG + 5 * 16384 + 8192,
                   V_TAB = V_STG + 6 * 16384 + 8192, V_PF = V_STG + 16384 + 12288, V_OX = V_STG + 16384 + 8192;
constexpr int OR = 10;
constexpr uint32_t K1_BAR = 229376, K1_SMEM = K1_BAR + 256;
static_assert(K1_SMEM <= 232448, "smem");
constexpr uint32_t MB_X = 0, MB_S = 16, MB_A = 32, MB_B = 64, MB_C = 96, MB_D = 128, MB_P = 160;
enum { B_MEM = 1, B_GOK = 2, B_QF = 3, B_W0 = 4, B_W1 = 5, B_GOX = 6, B_GOQ = 7, B_VM = 8, B_KM = 9, B_SX = 10, B_S = 11, B_PD = 12, B_RED = 2, B_P = 3, B_GOV = 6, B_OX = 7, B_XF = 8 };

__device__ __forceinline__ uint4 ld_rlx(const void* p) {
  uint4 v; asm volatile("ld.relaxed.gpu.global.v4.u32 {%0,%1,%2,%3}, [%4];" : "=r"(v.x), "=r"(v.y), "=r"(v.z), "=r"(v.w) : "l"(p) : "memory"); return v;
}
__device__ __forceinline__ void st_rlx(void* p, uint32_t a, uint32_t b, uint32_t c, uint32_t d) {
  asm volatile("st.relaxed.gpu.global.v4.u32 [%0], {%1,%2,%3,%4};" ::"l"(p), "r"(a), "r"(b), "r"(c), "r"(d) : "memory");
}
__device__ __forceinline__ void st_rlx64(void* p, uint32_t a, uint32_t b) { asm volatile("st.relaxed.gpu.global.v2.u32 [%0], {%1,%2};" ::"l"(p), "r"(a), "r"(b) : "memory"); }
__device__ __forceinline__ void st_rlx32(void* p, uint32_t v) { asm volatile("st.relaxed.gpu.global.u32 [%0], %1;" ::"l"(p), "r"(v) : "memory"); }
__device__ __forceinline__ uint32_t tagw(uint32_t w, uint32_t ph) { return (w & ~1u) | ph; }
__device__ __forceinline__ uint32_t fu(float x) { return __float_as_uint(x); }
__device__ __forceinline__ float uf(uint32_t x) { return __uint_as_float(x); }
__device__ __forceinline__ void mma16816(float (&c)[4], uint32_t a0, uint32_t a1, uint32_t a2, uint32_t a3, uint32_t b0, uint32_t b1) {
  asm volatile("mma.sync.aligned.m16n8k16.row.col.f32.bf16.bf16.f32 {%0,%1,%2,%3}, {%4,%5,%6,%7}, {%8,%9}, {%0,%1,%2,%3};"
               : "+f"(c[0]), "+f"(c[1]), "+f"(c[2]), "+f"(c[3]) : "r"(a0), "r"(a1), "r"(a2), "r"(a3), "r"(b0), "r"(b1));
}
__device__ __forceinline__ void mma16816z(float (&c)[4], uint32_t a0, uint32_t a1, uint32_t a2, uint32_t a3, uint32_t b0, uint32_t b1) {
  asm volatile("mma.sync.aligned.m16n8k16.row.col.f32.bf16.bf16.f32 {%0,%1,%2,%3}, {%4,%5,%6,%7}, {%8,%9}, {%10,%10,%10,%10};"
               : "=f"(c[0]), "=f"(c[1]), "=f"(c[2]), "=f"(c[3]) : "r"(a0), "r"(a1), "r"(a2), "r"(a3), "r"(b0), "r"(b1), "f"(0.f));
}
__device__ __forceinline__ void mma1688(float (&c)[4], uint32_t a0, uint32_t a1, uint32_t b0) {
  asm volatile("mma.sync.aligned.m16n8k8.row.col.f32.bf16.bf16.f32 {%0,%1,%2,%3}, {%4,%5}, {%6}, {%0,%1,%2,%3};"
               : "+f"(c[0]), "+f"(c[1]), "+f"(c[2]), "+f"(c[3]) : "r"(a0), "r"(a1), "r"(b0));
}
__device__ __forceinline__ void ldsm4(uint32_t (&r)[4], uint32_t a) {
  asm volatile("ldmatrix.sync.aligned.m8n8.x4.shared.b16 {%0,%1,%2,%3}, [%4];" : "=r"(r[0]), "=r"(r[1]), "=r"(r[2]), "=r"(r[3]) : "r"(a) : "memory");
}
__device__ __forceinline__ void ldsm4t(uint32_t (&r)[4], uint32_t a) {
  asm volatile("ldmatrix.sync.aligned.m8n8.x4.trans.shared.b16 {%0,%1,%2,%3}, [%4];" : "=r"(r[0]), "=r"(r[1]), "=r"(r[2]), "=r"(r[3]) : "r"(a) : "memory");
}
__device__ __forceinline__ void stsm4t(uint32_t a, uint32_t r0, uint32_t r1, uint32_t r2, uint32_t r3) {
  asm volatile("stmatrix.sync.aligned.m8n8.x4.trans.shared.b16 [%0], {%1,%2,%3,%4};" ::"r"(a), "r"(r0), "r"(r1), "r"(r2), "r"(r3) : "memory");
}
__device__ __forceinline__ uint32_t movm(uint32_t x) { uint32_t y; asm volatile("movmatrix.sync.aligned.m8n8.trans.b16 %0, %1;" : "=r"(y) : "r"(x)); return y; }
__device__ __forceinline__ float2 lds_f2(uint32_t a) { float2 v; asm volatile("ld.shared.v2.f32 {%0,%1}, [%2];" : "=f"(v.x), "=f"(v.y) : "r"(a) : "memory"); return v; }
__device__ __forceinline__ float4 lds_f4(uint32_t a) { float4 v; asm volatile("ld.shared.v4.f32 {%0,%1,%2,%3}, [%4];" : "=f"(v.x), "=f"(v.y), "=f"(v.z), "=f"(v.w) : "r"(a) : "memory"); return v; }
__device__ __forceinline__ void sts_v2(uint32_t a, uint32_t x, uint32_t y) { asm volatile("st.shared.v2.u32 [%0], {%1,%2};" ::"r"(a), "r"(x), "r"(y) : "memory"); }
__device__ __forceinline__ void sts_f4(uint32_t a, float x, float y, float z, float w) { asm volatile("st.shared.v4.f32 [%0], {%1,%2,%3,%4};" ::"r"(a), "f"(x), "f"(y), "f"(z), "f"(w) : "memory"); }
__device__ __forceinline__ void sta_f4(uint32_t a, float x, float y, float z, float w, uint32_t bar) {
  asm volatile("st.async.weak.shared::cluster.mbarrier::complete_tx::bytes.v4.f32 [%0], {%1,%2,%3,%4}, [%5];" ::"r"(a), "f"(x), "f"(y), "f"(z), "f"(w), "r"(bar) : "memory");
}
__device__ __forceinline__ void sta_u4(uint32_t a, uint32_t x, uint32_t y, uint32_t z, uint32_t w, uint32_t bar) {
  asm volatile("st.async.weak.shared::cluster.mbarrier::complete_tx::bytes.v4.b32 [%0], {%1,%2,%3,%4}, [%5];" ::"r"(a), "r"(x), "r"(y), "r"(z), "r"(w), "r"(bar) : "memory");
}
template <int O, int N> __device__ __forceinline__ void send8(uint32_t a, const float (&d)[N], uint32_t bar) {
  sta_u4(a, pack_bf16(d[O], d[O + 1]), pack_bf16(d[O + 2], d[O + 3]), pack_bf16(d[O + 4], d[O + 5]), pack_bf16(d[O + 6], d[O + 7]), bar);
}
template <int O, int N> __device__ __forceinline__ uint4 add8(const float (&d)[N], const uint4& p) {
  return make_uint4(pack_bf16(d[O] + bf_lo(p.x), d[O + 1] + bf_hi(p.x)), pack_bf16(d[O + 2] + bf_lo(p.y), d[O + 3] + bf_hi(p.y)),
                    pack_bf16(d[O + 4] + bf_lo(p.z), d[O + 5] + bf_hi(p.z)), pack_bf16(d[O + 6] + bf_lo(p.w), d[O + 7] + bf_hi(p.w)));
}
__device__ __forceinline__ void stsm4t(uint32_t a, const uint4& r) { stsm4t(a, r.x, r.y, r.z, r.w); }
__device__ __forceinline__ void sta_f2(uint32_t a, float x, float y, uint32_t bar) {
  asm volatile("st.async.weak.shared::cluster.mbarrier::complete_tx::bytes.v2.f32 [%0], {%1,%2}, [%3];" ::"r"(a), "f"(x), "f"(y), "r"(bar) : "memory");
}
__device__ __forceinline__ uint32_t mapa(uint32_t a, uint32_t r) { uint32_t o; asm volatile("mapa.shared::cluster.u32 %0, %1, %2;" : "=r"(o) : "r"(a), "r"(r)); return o; }
__device__ __forceinline__ void mbar_wait1(uint32_t bar, uint32_t parity) {
  asm volatile("{\n.reg .pred p;\n.reg .u32 c;\nmbarrier.try_wait.parity.shared::cta.b64 p, [%0], %1;\n@p bra.uni DONE;\nmov.u32 c, 0;\n"
               "AGAIN:\nmbarrier.try_wait.parity.shared::cta.b64 p, [%0], %1;\n@p bra.uni DONE;\nadd.u32 c, c, 1;\nsetp.lt.u32 p, c, 0x400000;\n@p bra.uni AGAIN;\nDONE:\n}"
               ::"r"(bar), "r"(parity) : "memory");
}
__device__ __forceinline__ void arrive_e(uint32_t bar) {
  asm volatile("{\n.reg .pred p;\nelect.sync _|p, 0xffffffff;\n@p mbarrier.arrive.shared::cta.b64 _, [%0];\n}" ::"r"(bar) : "memory");
}
__device__ __forceinline__ void expect_e(uint32_t bar, uint32_t bytes) {
  asm volatile("{\n.reg .pred p;\nelect.sync _|p, 0xffffffff;\n@p mbarrier.arrive.expect_tx.shared::cta.b64 _, [%0], %1;\n}" ::"r"(bar), "r"(bytes) : "memory");
}
__device__ __forceinline__ float ex2(float x) { float y; asm("ex2.approx.ftz.f32 %0, %1;" : "=f"(y) : "f"(x)); return y; }
__device__ __forceinline__ float rcp(float x) { float y; asm("rcp.approx.ftz.f32 %0, %1;" : "=f"(y) : "f"(x)); return y; }
__device__ __forceinline__ uint32_t phase_of(int n) { return (uint32_t)(((n >> 1) & 1) ^ 1); }
__device__ __forceinline__ uint32_t clk() { uint64_t c; asm volatile("mov.u64 %0, %%clock64;" : "=l"(c)::"memory"); return (uint32_t)c; }
__device__ __forceinline__ void wait_until(uint32_t t) {
  asm volatile("{\n.reg .pred p;\n.reg .u64 c;\n.reg .u32 l, h;\nAGAIN:\nmov.u64 c, %%clock64;\nmov.b64 {l, h}, c;\nsub.u32 l, l, %0;\nsetp.lt.s32 p, l, 0;\n@p bra.uni AGAIN;\n}" ::"r"(t) : "memory");
}
__device__ __forceinline__ void cluster_sync_all() { asm volatile("barrier.cluster.arrive.release.aligned;\nbarrier.cluster.wait.acquire.aligned;" ::: "memory"); }
__device__ __forceinline__ uint32_t side_off(uint32_t off, uint32_t c) { return off + (((c ^ __popc((off >> 12) & 0xb2u)) & 1u) << 12); }
#define SCHED() asm volatile("pmevent 1;" ::: "memory")
#define PIN64(x) asm volatile("" : "+l"(x))
#define PIN32(x) asm volatile("" : "+r"(x))

__device__ __forceinline__ uint32_t bad2(uint32_t a, uint32_t b, uint32_t ph) { uint32_t r; asm("lop3.b32 %0, %1, %2, %3, 0x7e;" : "=r"(r) : "r"(a), "r"(b), "r"(ph)); return r; }
__device__ __forceinline__ uint32_t or3(uint32_t a, uint32_t b, uint32_t c) { uint32_t r; asm("lop3.b32 %0, %1, %2, %3, 0xfe;" : "=r"(r) : "r"(a), "r"(b), "r"(c)); return r; }
template <int N> __device__ __forceinline__ bool tags_ok(const uint4 (&v)[N], uint32_t ph) {
  uint32_t bad;
  if constexpr (N == 2) bad = bad2(v[0].x, v[1].x, ph);
  if constexpr (N == 4) bad = or3(bad2(v[0].x, v[1].x, ph), bad2(v[2].x, v[3].x, ph), 0);
  if constexpr (N == 8) bad = or3(bad2(v[0].x, v[1].x, ph), bad2(v[2].x, v[3].x, ph), bad2(v[4].x, v[5].x, ph)), bad = or3(bad, bad2(v[6].x, v[7].x, ph), 0);
  return __all_sync(0xffffffffu, (bad & 1) == 0);
}
__device__ __forceinline__ void reload(uint4& v, const uint8_t* p, uint32_t ph) {
  asm volatile("{\n.reg .pred p;\n.reg .b32 t;\nxor.b32 t, %0, %5;\nand.b32 t, t, 1;\nsetp.ne.u32 p, t, 0;\n@p ld.relaxed.gpu.global.v4.u32 {%0,%1,%2,%3}, [%4];\n}"
               : "+r"(v.x), "+r"(v.y), "+r"(v.z), "+r"(v.w) : "l"(p), "r"(ph) : "memory");
}
__device__ __forceinline__ uint32_t lds_vol(uint32_t a) { uint32_t v; asm volatile("ld.volatile.shared.u32 %0, [%1];" : "=r"(v) : "r"(a) : "memory"); return v; }
#define DLY_UP 48
#define DLY_DN 16
__device__ __forceinline__ uint4 badd4(const uint4& a, const uint4& b) { return make_uint4(badd2(a.x, b.x), badd2(a.y, b.y), badd2(a.z, b.z), badd2(a.w, b.w)); }
template <int N, int ST> __device__ __forceinline__ void repoll(uint4 (&v)[N], const uint8_t* p0, const uint8_t* p1, uint32_t ph, int* dly = nullptr) {
  if (!tags_ok<N>(v, ph)) {
    if (dly) *dly = 1;
#pragma unroll 1
    for (int it = 0; it < POLL_MAX; it++) {
#pragma unroll
      for (int i = 0; i < N; i++) reload(v[i], (i < N / 2) ? p0 + i * ST : p1 + (i - N / 2) * ST, ph);
      if (tags_ok<N>(v, ph)) break;
    }
  }
#pragma unroll
  for (int i = 0; i < N; i++) asm volatile("" : "+r"(v[i].x), "+r"(v[i].y), "+r"(v[i].z), "+r"(v[i].w));
}
template <int N, int ST> __device__ __forceinline__ void poll(uint4 (&v)[N], const uint8_t* p0, const uint8_t* p1, uint32_t ph, int* dly = nullptr) {
#pragma unroll
  for (int i = 0; i < N; i++) v[i] = ld_rlx((i < N / 2) ? p0 + i * ST : p1 + (i - N / 2) * ST);
  repoll<N, ST>(v, p0, p1, ph, dly);
}
__device__ __forceinline__ uint4 tab(uint32_t tb, int k) {
  uint4 v; asm volatile("ld.volatile.shared.v4.u32 {%0,%1,%2,%3}, [%4];" : "=r"(v.x), "=r"(v.y), "=r"(v.z), "=r"(v.w) : "r"(tb + k * 4096) : "memory"); return v;
}
__device__ __forceinline__ uint32_t opaque(uint32_t slot, uint32_t v) { sts_u32(slot, v); return lds_vol(slot); }
__device__ __forceinline__ uint4 tabo(uint32_t a) { return tab(a, 0); }
__device__ __forceinline__ void quad_store(uint8_t* dst, const uint32_t (&ox)[4], int tq) {
  uint32_t a0 = ox[0], a1 = ox[1], a2 = ox[2], a3 = ox[3];
  const bool b0 = tq & 1, b1 = tq & 2;
  uint32_t s0 = b0 ? a0 : a1, s1 = b0 ? a2 : a3;
  s0 = __shfl_xor_sync(0xffffffffu, s0, 1); s1 = __shfl_xor_sync(0xffffffffu, s1, 1);
  if (b0) { a0 = s0; a2 = s1; } else { a1 = s0; a3 = s1; }
  uint32_t u0 = b1 ? a0 : a2, u1 = b1 ? a1 : a3;
  u0 = __shfl_xor_sync(0xffffffffu, u0, 2); u1 = __shfl_xor_sync(0xffffffffu, u1, 2);
  if (b1) { a0 = u0; a1 = u1; } else { a2 = u0; a3 = u1; }
  *reinterpret_cast<uint4*>(dst) = make_uint4(a0, a1, a2, a3);
}
__device__ __forceinline__ uint8_t* mkptr(uint32_t lo, uint32_t hi) { return reinterpret_cast<uint8_t*>(((uint64_t)hi << 32) | lo); }
__device__ __forceinline__ uint32_t plo(const void* p) { return (uint32_t)reinterpret_cast<uint64_t>(p); }
__device__ __forceinline__ uint32_t phi(const void* p) { return (uint32_t)(reinterpret_cast<uint64_t>(p) >> 32); }

#define TS(i) do { } while (0)
#define TSW(i, W) do { } while (0)
#define TSG(i) do { } while (0)
#define TSA(i) do { } while (0)
#define TS_DUMP() do { } while (0)
#define XSKIP 0
#define XSKIP_LO 0
#define XSKIP_X 0
#define NOATT 0
#define XPOS 0
#define DLY_Q 2000
#define DLY_V 250
#define DLY_O 2100

#define GOI 0
template <int H> __device__ __forceinline__ void proj2_pre(uint32_t (&at)[8][4], uint32_t wres) {
#pragma unroll
  for (int m = 0; m < 4; m++) ldsm4t(at[4 * H + m], wres + (2 * H + (m >> 1)) * 2048 + (m & 1) * 16384);
}
__device__ constexpr int p2_s(int i) { return i == 0 ? 0 : i == 1 ? 1 : i == 9 ? 2 : i == 14 ? 3 : -1; }
__device__ constexpr int p2_r(int i) { return i - 2 - (i > 9) - (i > 14); }
__device__ constexpr int p2_pair(int i) { return p2_s(i) >= 0 ? 12 + p2_s(i) : p2_r(i); }
#define VMI 17
template <int GO> __device__ __forceinline__ void proj2(float (&d)[8], const uint32_t (&wf)[2][KR][4], uint32_t (&at)[8][4], uint32_t wres, uint32_t mems) {
  float acc[2][2][4];
  uint32_t b[2][4];
  ldsm4(b[0], mems + p2_pair(0) * 512);
#pragma unroll
  for (int i = 0; i < 16; i++) {
    if (i + 1 < 16) ldsm4(b[(i + 1) & 1], mems + p2_pair(i + 1) * 512);
    if (i >= 2 && i < 6) ldsm4t(at[i - 2], wres + (4 + ((i - 2) >> 1)) * 2048 + ((i - 2) & 1) * 16384);
    if (i >= 7 && i < 12 && i != 9) { const int m = i - 7 - (i > 9); ldsm4t(at[4 + m], wres + (6 + (m >> 1)) * 2048 + (m & 1) * 16384); }
    const uint32_t (&bb)[4] = b[i & 1];
    if (GOI > 0 && i == GOI && GO) bar_arrive(GO, 256);
#pragma unroll
    for (int u = 0; u < 2; u++)
#pragma unroll
      for (int t = 0; t < 2; t++) {
        const uint32_t* a = (p2_s(i) < 0) ? wf[t][p2_s(i) < 0 ? 2 * p2_r(i) + u : 0] : at[(p2_s(i) & 1) * 4 + 2 * u + t];
        if (i == 0) mma16816z(acc[t][u], a[0], a[1], a[2], a[3], bb[2 * u], bb[2 * u + 1]);
        else mma16816(acc[t][u], a[0], a[1], a[2], a[3], bb[2 * u], bb[2 * u + 1]);
      }
  }
#pragma unroll
  for (int t = 0; t < 2; t++)
#pragma unroll
    for (int e = 0; e < 4; e++) d[4 * t + e] = acc[t][0][e] + acc[t][1][e];
}
constexpr uint32_t SMEM0 = 0x400;
__device__ constexpr uint64_t cdesc(uint32_t off) { return (0x40000040ull << 32) | 0x10000u | ((SMEM0 + off) >> 4); }
template <uint32_t AOFF, uint32_t XOFF, int K0 = 0, int K1 = 32, bool IL = true> __device__ __forceinline__ void xproj(float (&ax)[16], const uint32_t (&wf)[KR][4]) {
#pragma unroll
  for (int i = K0; i < (XSKIP && AOFF >= XSKIP_LO && XOFF >= XSKIP_X ? (K0 == 0 ? 1 : K0) : K1); i++) {
    const int ks = !IL ? i : ((i & 3) == 3) ? KR + (i >> 2) : 3 * (i >> 2) + (i & 3);
    if (ks < KR) wg_rs_n32<0>(ax, wf[ks < KR ? ks : 0][0], wf[ks < KR ? ks : 0][1], wf[ks < KR ? ks : 0][2], wf[ks < KR ? ks : 0][3], cdesc(XOFF) + (ks >> 2) * 256 + (ks & 3) * 2, i != 0);
    else wg_ss_n32_ta<0>(ax, cdesc(AOFF) + (ks - KR) * 128, cdesc(XOFF) + (ks >> 2) * 256 + (ks & 3) * 2, 1);
  }
  wg_commit();
}
__device__ __forceinline__ void wg_ss_n40(float (&d)[20], uint64_t da, uint64_t db, int sd) {
  asm volatile("{\n.reg .pred p;\nsetp.ne.b32 p, %22, 0;\n"
    "wgmma.mma_async.sync.aligned.m64n40k16.f32.bf16.bf16 {%0, %1, %2, %3, %4, %5, %6, %7, %8, %9, %10, %11, %12, %13, %14, %15, %16, %17, %18, %19}, %20, %21, p, 1, 1, 0, 0;\n}\n"
    : "+f"(d[0]), "+f"(d[1]), "+f"(d[2]), "+f"(d[3]), "+f"(d[4]), "+f"(d[5]), "+f"(d[6]), "+f"(d[7]), "+f"(d[8]), "+f"(d[9]), "+f"(d[10]), "+f"(d[11]), "+f"(d[12]), "+f"(d[13]),
      "+f"(d[14]), "+f"(d[15]), "+f"(d[16]), "+f"(d[17]), "+f"(d[18]), "+f"(d[19]) : "l"(da), "l"(db), "r"(sd));
}
__device__ constexpr uint64_t cdesc0(uint32_t off, uint32_t lbo) { return (8ull << 32) | ((uint64_t)(lbo >> 4) << 16) | ((SMEM0 + off) >> 4); }
template <int P> __device__ __forceinline__ void q_shadow(const uint32_t (&wf)[2][KR][4], uint32_t dst, uint32_t (&at)[8][4], uint32_t wres) {
  float ax[2][16];
  wg_fence();
  xproj<Q_WRES, Q_XT + P * 32768>(ax[0], wf[0]);
  xproj<Q_WRES + 16384, Q_XT + P * 32768, 0, 10>(ax[1], wf[1]);
  wg_wait<1>(); fence_regs(ax[0]);
  stsm4t(dst, pack_bf16(ax[0][0], ax[0][1]), pack_bf16(ax[0][2], ax[0][3]), pack_bf16(ax[0][4], ax[0][5]), pack_bf16(ax[0][6], ax[0][7]));
  stsm4t(dst + 256, pack_bf16(ax[0][8], ax[0][9]), pack_bf16(ax[0][10], ax[0][11]), pack_bf16(ax[0][12], ax[0][13]), pack_bf16(ax[0][14], ax[0][15]));
  proj2_pre<0>(at, wres); proj2_pre<1>(at, wres);
  xproj<Q_WRES + 16384, Q_XT + P * 32768, 10, 32>(ax[1], wf[1]);
  wg_wait<0>(); fence_regs(ax[1]);
  stsm4t(dst + 4096, pack_bf16(ax[1][0], ax[1][1]), pack_bf16(ax[1][2], ax[1][3]), pack_bf16(ax[1][4], ax[1][5]), pack_bf16(ax[1][6], ax[1][7]));
  stsm4t(dst + 4096 + 256, pack_bf16(ax[1][8], ax[1][9]), pack_bf16(ax[1][10], ax[1][11]), pack_bf16(ax[1][12], ax[1][13]), pack_bf16(ax[1][14], ax[1][15]));
}
#define NW 10
#define NW1 0
template <int P, class F1, class F> __device__ __forceinline__ void k_shadow(const uint32_t (&wf)[2][KR][4], const uint4& t5, const uint32_t& bar, uint32_t tb, uint4& t0,
                                                                             uint4 (&kx)[4], uint32_t& tgo, F1&& mid1, F&& mid) {
  float ax[2][16];
  wg_fence();
  if (NW1 > 0) xproj<Q_WRES + 32768, Q_XT + P * 32768, 0, NW1, false>(ax[0], wf[0]);
  mid1();
  wg_fence();
  if (NW > 0) xproj<Q_WRES + 32768, Q_XT + P * 32768, NW1, NW1 + NW, false>(ax[0], wf[0]);
  mid();
  wg_fence();
  xproj<Q_WRES + 32768, Q_XT + P * 32768, NW1 + NW, 32, false>(ax[0], wf[0]);
  xproj<Q_WRES + 49152, Q_XT + P * 32768, 0, 10>(ax[1], wf[1]);
  wg_wait<1>(); fence_regs(ax[0]);
  send8<0>(t5.x, ax[0], t5.y); send8<8>(t5.x + 512, ax[0], t5.y);
  xproj<Q_WRES + 49152, Q_XT + P * 32768, 10, 25>(ax[1], wf[1]);
  xproj<Q_WRES + 49152, Q_XT + P * 32768, 25, 32>(ax[1], wf[1]);
  t0 = tab(tb, 0);
  wg_wait<1>();
  bar_arrive(B_GOQ, 256);
  mbar_wait1(bar, P);
  const uint4 a0 = lds_v4(t5.z), b0 = lds_v4(t5.z + 512);
  wg_wait<0>(); fence_regs(ax[1]);
  send8<0>(t5.x + 1024, ax[1], t5.y + 32); send8<8>(t5.x + 1536, ax[1], t5.y + 32);
  kx[0] = add8<0>(ax[0], a0); kx[1] = add8<8>(ax[0], b0);
  bar_sync(B_SX, 256);
  tgo = lds_vol(tb + 12288 + 4);
  stsm4t(t5.w, kx[0]); stsm4t(t5.w + 256, kx[1]);
  mbar_wait1(bar + 32, P);
  const uint4 a = lds_v4(t5.z + 1024), b = lds_v4(t5.z + 1536);
  kx[2] = add8<0>(ax[1], a); kx[3] = add8<8>(ax[1], b);
}
template <int P, class F> __device__ __forceinline__ void v1_shadow(const uint32_t (&vf)[KR][4], const uint32_t& rex, const uint32_t& rb, F&& mid) {
  float ax[16];
  wg_fence();
  xproj<V_WRES + 16384, V_XT + P * 32768, 0, 25>(ax, vf);
  xproj<V_WRES + 16384, V_XT + P * 32768, 25, 32>(ax, vf);
  mid();
  wg_wait<1>();
  bar_arrive(B_GOV, 256);
  wg_wait<0>(); fence_regs(ax);
  send8<0>(rex, ax, rb); send8<8>(rex + 512, ax, rb);
}
template <int P> __device__ __forceinline__ void v0_shadow(const uint32_t (&vf)[KR][4], uint32_t ex, uint32_t bar, uint8_t* xp, uint32_t vs, uint32_t pn) {
  float ax[16];
  wg_fence();
  xproj<V_WRES, V_XT + P * 32768>(ax, vf);
  mbar_wait1(bar, P);
  const uint4 a = lds_v4(ex), b = lds_v4(ex + 512);
  wg_wait<0>(); fence_regs(ax);
  const uint4 c = add8<0>(ax, a), d = add8<8>(ax, b);
  st_rlx(xp, tagw(c.x, pn), c.z, d.x, d.z); st_rlx(xp + 512, tagw(c.y, pn), c.w, d.y, d.w);
  sts_v4(vs, make_uint4(c.x, c.z, d.x, d.z)); sts_v4(vs + 512, make_uint4(c.y, c.w, d.y, d.w));
}
__device__ __forceinline__ void load_x(uint32_t sb, uint32_t xt, const CUtensorMap* tmX, int n, int j) {
  const uint32_t bar = sb + K1_BAR + MB_X + 8 * (n & 1);
  asm volatile("{\n.reg .pred p;\nelect.sync _|p, 0xffffffff;\n@p mbarrier.arrive.expect_tx.shared::cta.b64 _, [%2], 32768;\n"
               "@p cp.async.bulk.tensor.3d.shared::cluster.global.mbarrier::complete_tx::bytes [%0], [%1, {%3, %4, %5}], [%2];\n}"
               ::"r"(sb + xt + (n & 1) * 32768), "l"(tmX), "r"(bar), "r"(0), "r"(n * SEG), "r"(j * 8) : "memory");
}
__device__ __noinline__ uint32_t probe_side(uint8_t* xw, uint32_t sb) {
  uint32_t best[2] = {1u << 30, 1u << 30};
  uint32_t* p[2] = {reinterpret_cast<uint32_t*>(xw + side_off(XW_PROBE, 0) + blockIdx.x * 32), reinterpret_cast<uint32_t*>(xw + side_off(XW_PROBE, 1) + blockIdx.x * 32)};
  st_rlx32(p[0], 0); st_rlx32(p[1], 0);
#pragma unroll 1
  for (int r = 0; r < 12; r++) {
    const uint32_t t0 = clk();
    uint32_t v; asm volatile("atom.relaxed.gpu.global.add.u32 %0, [%1], 1;" : "=r"(v) : "l"(p[r & 1]) : "memory");
    asm volatile("st.volatile.shared.u32 [%0], %1;" ::"r"(sb + K1_BAR + 248), "r"(v) : "memory");
    const uint32_t dt = clk() - t0;
    if (r & 1) best[1] = min(best[1], dt); else best[0] = min(best[0], dt);
  }
#define SIDEX 0
  return SIDEX == 2 ? 0 : (best[1] < best[0]) ^ SIDEX;
}

constexpr float SL2E = 0.08838834764831845f * 1.4426950408889634f;

template <int WG> __device__ __forceinline__ void qk_load_weights(uint32_t (&wf)[2][KR][4], uint32_t sb, const CUtensorMap* tm) {
  const int tid = threadIdx.x, lane = tid & 31, w = (tid >> 5) & 3, mi = lane >> 3, kr = (mi >> 1) * 8 + (lane & 7), h = blockIdx.x >> 2, j = blockIdx.x & 1;
  const uint32_t lo = kr * 128 + (((2 * w + (mi & 1)) ^ (kr & 7)) << 4), pb = sb + K1_BAR + MB_P + WG * 32, stg = sb + Q_STG + WG * 65536;
#pragma unroll
  for (int c = 0; c < 3; c++) {
    mbar_wait1(pb + 8 * c, 0);
#pragma unroll
    for (int t = 0; t < 2; t++)
#pragma unroll
      for (int ks = 0; ks < 8; ks++) ldsm4t(wf[t][8 * c + ks], stg + (2 * (c & 1) + t) * 16384 + ks * 2048 + lo);
    if (c == 0) {
      bar_sync(B_W0 + WG, 128);
      if ((tid & 127) == 0) {
        mbar_expect_tx(pb + 16, 32768);
        for (int t = 0; t < 2; t++) tma_load_2d(stg + t * 16384, tm, h * DH + 64 * t, j * 512 + 256, pb + 16);
      }
      __syncwarp();
    }
  }
  mbar_wait1(pb + 24, 0);
  TSG(2);
  cluster_sync_all();
}

__device__ __forceinline__ void role_q(uint32_t sb, const CUtensorMap* tmX, const CUtensorMap* tmW, uint8_t* __restrict__ xw) {
  uint32_t wf[2][KR][4];
  qk_load_weights<0>(wf, sb, tmW);
  const uint32_t tb0 = sb + Q_TAB + threadIdx.x * 16;
  {
    const uint32_t tb = tb0;
    const int h = blockIdx.x >> 2, j = blockIdx.x & 1, lane = threadIdx.x & 31, w = threadIdx.x >> 5, mi = lane >> 3, r8 = lane & 7, kr = (mi >> 1) * 8 + r8;
    const uint32_t BAR = sb + K1_BAR, l16 = sb + lane * 16, qex = l16 + Q_QEX + w * 512, bq = BAR + MB_A + 8 * w;
    const uint8_t* vxp = xw + XW_VX + (2 * h + j) * 4096 + w * 1024 + lane * 16;
    const uint8_t* op = xw + XW_O + (h >> 1) * 8192 + (4 * (h & 1) + 2 * j + (w >> 1)) * 512 + (lane >> 2) * 64 + (w & 1) * 32 + (lane & 3) * 8;
    sts_v4(tb, make_uint4(sb + Q_WRES + kr * 128 + (((2 * w + (mi & 1)) ^ (kr & 7)) << 4), l16, mapa(qex, j ^ 1), mapa(bq, j ^ 1)));
    sts_v4(tb + 4096, make_uint4(plo(vxp), phi(vxp), sb + Q_KX + mi * 640 + (8 * w + r8) * 16, bq));
    sts_v4(tb + 8192, make_uint4(qex, sb + Q_QF + (8 * (mi >> 1) + 2 * w + (mi & 1)) * 128 + r8 * 16, sb + Q_QF + (2 * (mi & 1) + (mi >> 1)) * 128 + r8 * 16, l16 + Q_SMX + (w >> 1) * 512 + (w & 1) * 8));
    sts_v4(tb + 12288, make_uint4(plo(op), phi(op), l16 + Q_SMM, sb + Q_VM + w * 256 + lane * 8));
    sts_v4(tb + 16384, make_uint4(BAR, (lane & 1) ? 0u : 1u, l16 + Q_SMX, sb + Q_QX + (2 * w + (mi & 1)) * 512 + (8 * (mi >> 1) + r8) * 16));
  }
  const uint32_t tb = opaque(tb0 + 20480, tb0);
  const int wu = __shfl_sync(0xffffffffu, threadIdx.x >> 5, 0);
  bar_arrive(B_SX, 256);
#pragma unroll 1
  for (int s = 0; s < NSEG; s++) {
    {
      float q[8];
      {
        const uint4 t4 = tab(tb, 4), t0 = tab(tb, 0);
        expect_e(t4.x + MB_A + 8 * wu, 512);
        if (wu == 0) {
          if (s + 1 < NSEG) load_x(t4.x - K1_BAR, Q_XT, tmX, s + 1, blockIdx.x & 1);
        }
        mbar_wait1(t4.x + MB_X + 8 * (s & 1), (s >> 1) & 1);
        bar_sync(B_GOQ, 256);
        TS(6);
        uint32_t at[8][4];
        if (s & 1) q_shadow<1>(wf, t4.w, at, t0.x); else q_shadow<0>(wf, t4.w, at, t0.x);
        TS(7);
        bar_sync(B_MEM, 256);
        proj2<B_GOK>(q, wf, at, t0.x, t0.y + Q_MEMS);
        send8<0>(t0.z, q, t0.w);
        if (NW1 > 0) bar_arrive(B_PD, 256);
      }
      SCHED();
      TS(1);
      const uint32_t ph = phase_of(s), par = s & 1;
      const uint4 t1 = tab(tb, 1), t2 = tab(tb, 2), t3 = tab(tb, 3), t4 = tab(tb, 4);
      const uint8_t* vxp = mkptr(t1.x ^ (par << 20), t1.y);
      uint4 vx[2];
      vx[0] = ld_rlx(vxp); vx[1] = ld_rlx(vxp + 512);
      uint32_t kx[4][4];
#pragma unroll
      for (int i = 0; i < 4; i++) ldsm4(kx[i], t1.z + i * 2560);
      uint8_t* op = mkptr(t3.x ^ (par << 20), t3.y);
      const uint32_t tbit = t4.y & ph;
      SCHED();
      mbar_wait1(t1.w, par);
      stsm4t(t2.y, add8<0>(q, lds_v4(t2.x)));
      bar_arrive(B_QF, 256);
      bar_sync(B_W1, 128);
      {
        float c[4][4];
        uint32_t a[4][4];
#pragma unroll
        for (int i = 0; i < 4; i++) ldsm4(a[i], t2.z + i * 512);
#pragma unroll
        for (int i = 0; i < 2; i++) {
          mma16816z(c[2 * i], a[i][0], a[i][1], a[i][2], a[i][3], kx[i][0], kx[i][1]);
          mma16816z(c[2 * i + 1], a[i][0], a[i][1], a[i][2], a[i][3], kx[i][2], kx[i][3]);
        }
#pragma unroll
        for (int i = 2; i < 4; i++) {
          mma16816(c[2 * i - 4], a[i][0], a[i][1], a[i][2], a[i][3], kx[i][0], kx[i][1]);
          mma16816(c[2 * i - 3], a[i][0], a[i][1], a[i][2], a[i][3], kx[i][2], kx[i][3]);
        }
        sts_v2(t2.w, fu((c[0][0] + c[1][2]) + (c[2][0] + c[3][2])), fu((c[0][1] + c[1][3]) + (c[2][1] + c[3][3])));
      }
      TS(2);
      const bool vok = tags_ok<2>(vx, ph);
      bar_sync(B_S, 256);
      {
        const float4 sa = lds_f4(t4.z), sb2 = lds_f4(t4.z + 512), r0 = lds_f4(t3.z), r1 = lds_f4(t3.z + 512);
        float e[10] = {sa.x, sa.y, sa.z, sa.w, sb2.x, sb2.y, sb2.z, sb2.w, (r0.x + r0.z) + (r1.x + r1.z), (r0.y + r0.w) + (r1.y + r1.w)};
        float mx = fmaxf(fmaxf(fmaxf(fmaxf(e[0], e[1]), fmaxf(e[2], e[3])), fmaxf(fmaxf(e[4], e[5]), fmaxf(e[6], e[7]))), fmaxf(e[8], e[9]));
        mx = fmaxf(mx, __shfl_xor_sync(0xffffffffu, mx, 1));
        mx = fmaxf(mx, __shfl_xor_sync(0xffffffffu, mx, 2));
        if (!vok) poll<2, 512>(vx, vxp, vxp + 512, ph);
        mx *= SL2E;
#pragma unroll
        for (int i = 0; i < 10; i++) e[i] = ex2(fmaf(e[i], SL2E, -mx));
        const uint32_t p0 = pack_bf16(e[0], e[1]), p1 = pack_bf16(e[2], e[3]), p2 = pack_bf16(e[4], e[5]), p3 = pack_bf16(e[6], e[7]), pm = pack_bf16(e[8], e[9]);
        float acc[3][4], u0[4], u1[4];
        TS(3);
        SCHED();
        bar_sync(B_VM, 256);
        const float2 vm = lds_f2(t3.w);
        mma16816z(acc[2], p0, p2, p1, p3, 0x3F803F80u, 0x3F803F80u);
        mma16816z(acc[0], p0, p2, p1, p3, vx[0].x, vx[0].y);
        mma16816z(acc[1], p0, p2, p1, p3, vx[1].x, vx[1].y);
        mma16816z(u0, p0, p2, p1, p3, vx[0].z, vx[0].w);
        mma16816z(u1, p0, p2, p1, p3, vx[1].z, vx[1].w);
        mma1688(acc[2], pm, 0u, 0x3F803F80u);
        mma1688(acc[0], pm, 0u, fu(vm.x));
        mma1688(acc[1], pm, 0u, fu(vm.y));
        const float inv = rcp(acc[2][0] + acc[2][2]);
        const uint32_t o0 = (pack_bf16((acc[0][0] + u0[2]) * inv, (acc[0][1] + u0[3]) * inv) & ~t4.y) | tbit, o1 = pack_bf16((acc[1][0] + u1[2]) * inv, (acc[1][1] + u1[3]) * inv);
        st_rlx64(op, o0, o1); st_rlx64(op + 4096, o0, o1);
      }
      bar_arrive(B_GOX, 256);
      SCHED();
      TS(5);
      TSA(12 + (threadIdx.x >> 5));
      {
        float c[20];
        fence_async_smem();
        bar_sync(B_KM, 256);
        wg_fence();
#pragma unroll
        for (int ks = 0; ks < 8; ks++) wg_ss_n40(c, cdesc0(Q_QX + ks * 1024, 512), cdesc0(Q_KX + ks * 1280, 640), ks != 0);
        wg_commit();
        uint4* sxp = &g_sx[par][(blockIdx.x >> 2) * 2 + (blockIdx.x & 1)][threadIdx.x & 31];
        wg_wait<0>(); fence_regs(c);
        bar_arrive(B_SX, 256);
        if (wu < 2) {
          sxp += wu * 64;
          st_rlx(sxp, tagw(fu(c[0]), ph), fu(c[1]), fu(c[4]), fu(c[5]));
          st_rlx(sxp + 32, tagw(fu(c[2]), ph), fu(c[3]), fu(c[6]), fu(c[7]));
          st_rlx(sxp + 192 - wu * 32, tagw(fu(c[16]), ph), fu(c[17]), fu(c[18]), fu(c[19]));
          if (wu == 1) {
            st_rlx(sxp + 64, tagw(fu(c[8]), ph), fu(c[9]), fu(c[12]), fu(c[13]));
            st_rlx(sxp + 96, tagw(fu(c[10]), ph), fu(c[11]), fu(c[14]), fu(c[15]));
          }
        }
      }
    }
  }
}

__device__ __forceinline__ void role_k(uint32_t sb, const CUtensorMap* tmW, uint8_t* __restrict__ xw, const bf16* __restrict__ mem0) {
  uint32_t wf[2][KR][4];
  qk_load_weights<1>(wf, sb, tmW);
  const uint32_t tb0 = sb + Q_TAB + threadIdx.x * 16;
  {
    const uint32_t tb = tb0;
    const int h = blockIdx.x >> 2, j = blockIdx.x & 1, lane = threadIdx.x & 31, w = (threadIdx.x >> 5) & 3, mi = lane >> 3, r8 = lane & 7, kr = (mi >> 1) * 8 + r8;
    const uint32_t BAR = sb + K1_BAR, l16 = sb + lane * 16, side = lds_u32(BAR + 240);
    const uint8_t* p0 = xw + (w & 1) * 2048 + lane * 16 + side_off(XW_MEM + (j * 4 + (w >> 1)) * 8192, side);
    const uint8_t* vp = xw + side_off(XW_VM + (2 * h + j) * 8192, side) + w * 512 + lane * 16;
    const uint32_t smm = sb + Q_SMM + (w >> 1) * 512 + lane * 16 + (w & 1) * 8, kex = l16 + Q_KEX + w * 512, ex = l16 + Q_KXEX + w * 2048;
    sts_v4(tb, make_uint4(sb + Q_WRES + 32768 + kr * 128 + (((2 * w + (mi & 1)) ^ (kr & 7)) << 4), l16 + Q_MEMS + w * 2048, plo(p0), phi(p0)));
    sts_v4(tb + 4096, make_uint4(kex, BAR + MB_B + 8 * w, smm, sb + Q_QF + (8 * (mi & 1) + 2 * w + (mi >> 1)) * 128 + r8 * 16));
    sts_v4(tb + 8192, make_uint4(mapa(kex, j ^ 1), mapa(BAR + MB_B + 8 * w, j ^ 1), plo(vp), phi(vp)));
    sts_v4(tb + 16384, make_uint4(kex, BAR + MB_B + 8 * w, sb + Q_KX + (8 * (mi >> 1) + 2 * w + (mi & 1)) * 640 + (32 + r8) * 16, sb + Q_VM + w * 256 + lane * 8));
    sts_v4(tb + 20480, make_uint4(mapa(ex, j ^ 1), mapa(BAR + MB_C + 8 * w, j ^ 1), ex, sb + Q_KX + (2 * w + (mi & 1)) * 640 + (8 * (mi >> 1) + r8) * 16));
    sts_v4(tb + 24576, make_uint4(w < 2 ? 0 : sb + Q_KX + mi * 640 + (32 + r8) * 16, l16 + Q_MEMS, BAR, BAR + MB_C + 8 * w));
#pragma unroll
    for (int i = 0; i < 4; i++) sts_v4(l16 + Q_MEMS + w * 2048 + i * 512, ldg_nc_v4(mem0 + r8 * DM + j * 512 + (16 * w + 4 * i + mi) * 8));
  }
  const uint32_t tb = opaque(sb + Q_SMX + (threadIdx.x & 127) * 4, tb0);
  sts_u32(tb + 12288, DLY_Q);
  auto finish = [&](int s, uint4 (&vm)[2], const uint4& kf) {
    const uint4 t4 = tab(tb, 4);
    const uint8_t* vp = mkptr(lds_vol(tb + 8192 + 8) ^ ((s & 1) << 20), lds_vol(tb + 8192 + 12));
    repoll<2, 512>(vm, vp, vp + 2048, phase_of(s));
    sts_v2(t4.w, pack_bf16(uf(vm[0].x) + uf(vm[1].x), uf(vm[0].y) + uf(vm[1].y)), pack_bf16(uf(vm[0].z) + uf(vm[1].z), uf(vm[0].w) + uf(vm[1].w)));
    bar_arrive(B_VM, 256);
    TSW(12, 7);
    stsm4t(t4.z, kf);
    fence_async_smem();
    bar_arrive(B_KM, 256);
  };
  float k[8] = {};
  auto scores = [&](int s, uint4 (&vm)[2], uint4& kf) {
    const uint4 t1 = tab(tb, 1);
    const uint8_t* vp = mkptr(lds_vol(tb + 8192 + 8) ^ ((s & 1) << 20), lds_vol(tb + 8192 + 12));
    mbar_wait1(t1.y, s & 1);
    const uint4 kp = lds_v4(t1.x);
    vm[0] = ld_rlx(vp); vm[1] = ld_rlx(vp + 2048);
    kf = add8<0>(k, kp);
    const uint32_t b0 = movm(kf.x), b1 = movm(kf.y), b2 = movm(kf.z), b3 = movm(kf.w);
    bar_sync(B_QF, 256);
    uint32_t a[4];
    ldsm4(a, t1.w);
    float c0[4], c1[4];
    mma16816z(c0, a[0], a[1], a[2], a[3], b0, b1);
    mma16816z(c1, a[0], a[1], a[2], a[3], b2, b3);
    sts_v2(t1.z, fu(c0[0] + c1[2]), fu(c0[1] + c1[3]));
    bar_sync(B_S, 256);
  };
  mbar_wait1(sb + K1_BAR + MB_X, 0);
#pragma unroll 1
  for (int s = 0; s < NSEG; s++) {
    const uint32_t par = s & 1;
    uint32_t rk, rb;
    {
      uint4 vm[2] = {}, kf = {};
      auto mid1 = [&]() { if (s > 0) scores(s - 1, vm, kf); };
      uint4 t5, t0, kx[4];
      uint32_t tgo, bc;
      auto mid = [&]() {
        if (s > 0) finish(s - 1, vm, kf);
        t5 = tab(tb, 5); bc = lds_vol(tb + 24576 + 12);
        const int dq0 = max((int)lds_vol(tb + 12288) - DLY_DN, 0);
        expect_e(bc, 1024); expect_e(bc + 32, 1024); expect_e(bc - 32, 512);
        if (NW1 + NW == 0) mbar_wait1(sb + K1_BAR + MB_X + 8 * par, (s >> 1) & 1);
        if (s > 0) bar_sync(B_GOX, 256);
        sts_v2(tb + 12288, dq0, clk() + dq0);
      };
      if (par) k_shadow<1>(wf, t5, bc, tb, t0, kx, tgo, mid1, mid); else k_shadow<0>(wf, t5, bc, tb, t0, kx, tgo, mid1, mid);
      const uint8_t* p0 = mkptr(t0.z ^ ((par ^ 1) << 20), t0.w);
      uint4 v[8];
      wait_until(tgo);
      int dq = 0;
#pragma unroll
      for (int i = 0; i < 8; i++) v[i] = ld_rlx(p0 + (i & 3) * 512 + (i >> 2) * 16384);
      stsm4t(t5.w + 5120, kx[2]); stsm4t(t5.w + 5120 + 256, kx[3]);
      uint32_t at[8][4];
      proj2_pre<0>(at, t0.x);
      TS(15);
      if (s > 0) {
        repoll<8, 512>(v, p0, p0 + 16384, phase_of(s - 1), &dq);
#pragma unroll
        for (int i = 0; i < 4; i++) sts_v4(t0.y + i * 512, badd4(v[i], v[i + 4]));
      }
      TSA(4 + (threadIdx.x >> 5));
      bar_arrive(B_MEM, 256);
      if (dq) asm volatile("red.shared.add.u32 [%0], %1;" ::"r"(tb + 12288), "r"(DLY_UP + DLY_DN) : "memory");
      const uint32_t mems = lds_vol(tb + 24576 + 4);
      proj2_pre<1>(at, t0.x);
      rk = lds_vol(tb + 8192); rb = lds_vol(tb + 8192 + 4);
      TS(9);
      if (GOI > 0) bar_sync(B_GOK, 256); else bar_sync(B_GOK, 128);
      proj2<0>(k, wf, at, t0.x, mems);
    }
    send8<0>(rk, k, rb);
    if (NW1 + NW > 0 && s + 1 < NSEG) mbar_wait1(sb + K1_BAR + MB_X + 8 * (par ^ 1), ((s + 1) >> 1) & 1);
    if (NW1 > 0) bar_sync(B_PD, 256);
    TS(10);
  }
  uint4 vm[2], kf;
  scores(NSEG - 1, vm, kf);
  finish(NSEG - 1, vm, kf);
  bar_sync(B_GOX, 256);
  bar_sync(B_SX, 256);
}

template <int WG> __device__ __forceinline__ void role_v(uint32_t sb, const CUtensorMap* tmX, const CUtensorMap* tmWo, const CUtensorMap* tmOx, uint8_t* __restrict__ xw, const bf16* __restrict__ mem0) {
  uint32_t vf[KR][4], of[2][OR][4];
  const uint32_t BAR = sb + K1_BAR;
  const int h = blockIdx.x >> 2, j = blockIdx.x & 1;
  {
    const int tid = threadIdx.x, lane = tid & 31, w = (tid >> 5) & 3, mi = lane >> 3, kr = (mi >> 1) * 8 + (lane & 7), g = lane >> 2, tq = lane & 3;
    const uint32_t lo = kr * 128 + (((2 * w + (mi & 1)) ^ (kr & 7)) << 4), pb = BAR + MB_P + WG * 32, stg = sb + V_STG + WG * 65536;
    mbar_wait1(pb, 0);
    TSG(2);
#pragma unroll
    for (int ks = 0; ks < KR; ks++) ldsm4t(vf[ks], stg + ks * 2048 + lo);
    bar_sync(B_W0 + WG, 128);
    if ((tid & 127) == 0) {
      mbar_expect_tx(pb + 8, 65536);
      for (int c = 0; c < 4; c++) tma_load_2d(stg + c * 16384, tmWo, 32 * h, 2048 * j + 1024 * WG + 256 * c, pb + 8);
    }
    __syncwarp();
    mbar_wait1(pb + 8, 0);
    TSG(3);
    const uint32_t src = stg + w * 16384 + (16 * (tq >> 1) + 4 * (tq & 1)) * 64 + g * 4;
    uint32_t tmp[2 * (16 - OR)][4];
#pragma unroll
    for (int ks = 0; ks < 16; ks++)
#pragma unroll
      for (int mt = 0; mt < 2; mt++) {
        const uint32_t a = src + (32 * (ks >> 1) + 2 * (ks & 1)) * 64 + mt * 32;
        const uint32_t w0 = lds_u32(a), w1 = lds_u32(a + 64), w2 = lds_u32(a + 512), w3 = lds_u32(a + 576);
        const int pi = ks >> 1, si = (pi == 0) ? 0 : (pi == 3) ? 1 : (pi == 6) ? 2 : -1, ri = pi - 1 - (pi > 3) - (pi > 6);
        uint32_t (&f)[4] = (si < 0) ? of[mt][si < 0 ? 2 * ri + (ks & 1) : 0] : tmp[si < 0 ? 0 : 4 * si + 2 * (ks & 1) + mt];
        f[0] = prmt(w0, w1, 0x5410u); f[1] = prmt(w0, w1, 0x7632u); f[2] = prmt(w2, w3, 0x5410u); f[3] = prmt(w2, w3, 0x7632u);
      }
    __syncwarp();
#pragma unroll
    for (int i = 0; i < 2 * (16 - OR); i++) sts_v4(stg + w * 16384 + i * 512 + lane * 16, make_uint4(tmp[i][0], tmp[i][1], tmp[i][2], tmp[i][3]));
  }
  TSG(4);
  cluster_sync_all();
  constexpr int T2 = WG ? 16384 - 2048 : -12288, T3 = T2 + 2048, T4 = -12288;
  uint32_t tb;
  {
    const int lane = threadIdx.x & 31, w = (threadIdx.x >> 5) & 3, warp = 4 * WG + w, mi = lane >> 3, r8 = lane & 7, kr = (mi >> 1) * 8 + r8, g = lane >> 2, tq = lane & 3;
    const uint32_t l16 = sb + lane * 16, side = lds_u32(BAR + 240), t = sb + V_TAB + threadIdx.x * 16, ex = l16 + V_VXEX + w * 16384;
    sts_v4(t, make_uint4(w * 1024 + lane * 16 + side_off(XW_MEM + (j * 4 + WG) * 8192, side), XW_VM + (2 * h + (WG ^ j)) * 8192 + j * 2048 + w * 512 + lane * 16,
                         l16 + V_MEMS + warp * 1024, sb + V_WRES + WG * 16384 + kr * 128 + (((2 * w + (mi & 1)) ^ (kr & 7)) << 4)));
    sts_v4(t + 4096, make_uint4(side_off(XW_O + (8 * j + warp) * 8192, side) + lane * 16 + 2048,
                                XW_MEM + ((h >> 4) * 4 + j * 2 + ((h >> 3) & 1)) * 8192 + (h & 7) * 512 + w * 128 + r8 * 16 + mi * 4,
                                l16 + V_STG + warp * 16384, sb + V_STG + V_RED + w * 256 + lane * 8));
    if (WG == 0) {
      sts_v4(t + T2, make_uint4(XW_VX + (2 * h + j) * 4096 + w * 1024 + lane * 16, l16 + V_VXS + w * 1024, ex, BAR + MB_A + 8 * w));
    } else {
      const int orow = 8 * (mi & 1) + r8;
      sts_v4(t + T2, make_uint4(mapa(ex, j ^ 1), mapa(BAR + MB_A + 8 * w, j ^ 1), l16 + V_VXS + w * 1024, l16 + V_PS));
      sts_v4(t + T3, make_uint4(2 * h * 4096 + (w & 1) * 512 + lane * 16, l16 + V_PF + w * 16384, l16 + V_PS + (w >> 1) * 1536 + (w & 1) * 4, l16 + V_STG + w * 16384 + 7168));
      sts_v4(t + T4, make_uint4(XW_VM + (2 * h + j) * 8192 + w * 512 + lane * 16, sb + V_OX + orow * 128 + (((2 * w + (mi >> 1)) ^ r8) << 4), 0, 0));
      const int lim = 8 * w + g - 2 * tq;
#pragma unroll
      for (int i = 0; i < 2; i++)
        sts_v4(l16 + V_STG + w * 16384 + 7168 + i * 512, make_uint4(16 * i > lim ? 0xff800000u : 0u, 16 * i + 1 > lim ? 0xff800000u : 0u, 16 * i + 8 > lim ? 0xff800000u : 0u, 16 * i + 9 > lim ? 0xff800000u : 0u));
    }
#pragma unroll
    for (int i = 0; i < 2; i++) sts_v4(l16 + V_MEMS + warp * 1024 + i * 512, ldg_nc_v4(mem0 + r8 * DM + j * 512 + (8 * warp + 4 * i + mi) * 8));
    tb = opaque(l16 + V_STG + warp * 16384 + V_RED, t);
  }
  const int wu = __shfl_sync(0xffffffffu, (threadIdx.x >> 5) & 3, 0);
  uint32_t tpub = 0;
  int dv = DLY_V, dop = DLY_O;
#pragma unroll 1
  for (int s = -1; s <= NSEG; s++) {
    const uint32_t ph = phase_of(s), slot = (s & 1) * XW_SLOT;
    const int n = s + 1, a = s - 1;
    const uint32_t pa = phase_of(a);
    uint32_t tm = 0;
    if (WG == 1 && s >= 1) {
      const uint4 t3 = tabo(tb + T3);
      const uint8_t* p0 = reinterpret_cast<const uint8_t*>(&g_sx[a & 1][0][0]) + t3.x;
      const uint8_t* vp = xw + (lds_vol(tb + T4) + (slot ^ XW_SLOT));
#pragma unroll
      for (int p = 0; p < 2; p++) {
        cp_async16(t3.y + (4 * p) * 512, p0 + p * 4096 + (wu >> 1) * 1024); cp_async16(t3.y + (4 * p + 1) * 512, p0 + p * 4096 + (wu >> 1) * 2048);
        cp_async16(t3.y + (4 * p + 2) * 512, p0 + p * 4096 + (6 + (wu >> 1) - (wu & 1)) * 512); cp_async16(t3.y + (4 * p + 3) * 512, vp + p * 2048);
      }
    }
    if (s >= 0 && s < NSEG) {
      const uint4 t0 = tab(tb, 0);
      uint32_t at[8][4];
#pragma unroll
      for (int i = 0; i < 8; i++) ldsm4t(at[i], t0.w + i * 2048);
      uint8_t* vp = xw + (t0.y + slot);
      const uint32_t mems = sb + V_MEMS + (t0.z & 511);
      int failed = 0;
      if (s > 0) {
        const uint8_t* p0 = xw + (t0.x + (slot ^ XW_SLOT));
        SCHED();
        wait_until(tpub);
        uint4 v[4];
        poll<4, 512>(v, p0, p0 + 16384, phase_of(s - 1), &failed);
#pragma unroll
        for (int i = 0; i < 2; i++) sts_v4(t0.z + i * 512, badd4(v[i], v[i + 2]));
      }
      bar_sync(B_MEM, 256);
      TSW(16, 0);
      {
        float acc[4][4];
        uint32_t b[3][4];
        ldsm4(b[0], mems + 12 * 512); ldsm4(b[1], mems + 13 * 512);
#pragma unroll
        for (int i = 0; i < 16; i++) {
          const int p = (i + 12) & 15;
          if (i + 2 < 16) ldsm4(b[(i + 2) % 3], mems + ((p + 2) & 15) * 512);
#pragma unroll
          for (int u = 0; u < 2; u++) {
            const int ks = 2 * p + u;
            const uint32_t (&a)[4] = (ks < KR) ? vf[ks < KR ? ks : 0] : at[ks < KR ? 0 : ks - KR];
            if (i < 2) mma16816z(acc[ks & 3], a[0], a[1], a[2], a[3], b[i % 3][2 * u], b[i % 3][2 * u + 1]);
            else mma16816(acc[ks & 3], a[0], a[1], a[2], a[3], b[i % 3][2 * u], b[i % 3][2 * u + 1]);
          }
        }
        const uint32_t c0 = tagw(fu((acc[0][0] + acc[1][0]) + (acc[2][0] + acc[3][0])), ph), c1 = fu((acc[0][1] + acc[1][1]) + (acc[2][1] + acc[3][1])),
                       c2 = fu((acc[0][2] + acc[1][2]) + (acc[2][2] + acc[3][2])), c3 = fu((acc[0][3] + acc[1][3]) + (acc[2][3] + acc[3][3]));
        st_rlx(vp, c0, c1, c2, c3); st_rlx(vp + 4096, c0, c1, c2, c3);
      }
      SCHED();
      dv = max(dv + (failed ? DLY_UP : -DLY_DN), 0);
      tm = clk() + dop;
      TSW(17, 0);
    }
    if constexpr (WG == 0) {
      if (n < NSEG) {
        const uint4 t2 = tabo(tb + T2);
        if (wu == 0 && n + 1 < NSEG) load_x(sb, V_XT, tmX, n + 1, j);
        expect_e(t2.w, 1024);
        mbar_wait1(BAR + MB_X + 8 * (n & 1), (n >> 1) & 1);
        uint8_t* xp = xw + (t2.x + (slot ^ XW_SLOT));
        const uint32_t vs = t2.y + (n % 3) * 16384;
        bar_sync(B_GOV, 256);
        if (n & 1) v0_shadow<1>(vf, t2.z, t2.w, xp, vs, phase_of(n)); else v0_shadow<0>(vf, t2.z, t2.w, xp, vs, phase_of(n));
      }
    } else {
      uint4 t2, t3, v[8];
      float4 ba, bb;
      auto fetch = [&]() {
        t2 = tabo(tb + T2); t3 = tabo(tb + T3);
        asm volatile("cp.async.wait_all;" ::: "memory");
#pragma unroll
        for (int i = 0; i < 8; i++) v[i] = lds_v4(t3.y + i * 512);
        ba = lds_f4(t3.w); bb = lds_f4(t3.w + 512);
      };
      if (n < NSEG) {
        mbar_wait1(BAR + MB_X + 8 * (n & 1), (n >> 1) & 1);
        if (n & 1) v1_shadow<1>(vf, t2.x, t2.y, fetch); else v1_shadow<0>(vf, t2.x, t2.y, fetch);
      } else fetch();
      if (s >= 1 && !NOATT) {
        if (!tags_ok<8>(v, pa)) {
          const uint8_t* p0 = reinterpret_cast<const uint8_t*>(&g_sx[a & 1][0][0]) + t3.x;
          const uint8_t* vp = xw + (lds_vol(tb + T4) + (slot ^ XW_SLOT));
#pragma unroll 1
          for (int it = 0; it < POLL_MAX; it++) {
#pragma unroll
            for (int p = 0; p < 2; p++) {
              v[4 * p] = ld_rlx(p0 + p * 4096 + (wu >> 1) * 1024); v[4 * p + 1] = ld_rlx(p0 + p * 4096 + (wu >> 1) * 2048);
              v[4 * p + 2] = ld_rlx(p0 + p * 4096 + (6 + (wu >> 1) - (wu & 1)) * 512); v[4 * p + 3] = ld_rlx(vp + p * 2048);
            }
            if (tags_ok<8>(v, pa)) break;
          }
        }
#pragma unroll
        for (int i = 0; i < 8; i++) asm volatile("" : "+r"(v[i].x), "+r"(v[i].y), "+r"(v[i].z), "+r"(v[i].w));
        const uint32_t vm0 = pack_bf16(uf(v[3].x) + uf(v[7].x), uf(v[3].y) + uf(v[7].y)), vm1 = pack_bf16(uf(v[3].z) + uf(v[7].z), uf(v[3].w) + uf(v[7].w));
        const bool hf = wu & 1;
        float e[10] = {fmaf(uf(v[0].x) + uf(v[4].x), SL2E, ba.x), fmaf(uf(v[0].y) + uf(v[4].y), SL2E, ba.y), fmaf(uf(v[0].z) + uf(v[4].z), SL2E, ba.z), fmaf(uf(v[0].w) + uf(v[4].w), SL2E, ba.w),
                       fmaf(uf(v[1].x) + uf(v[5].x), SL2E, bb.x), fmaf(uf(v[1].y) + uf(v[5].y), SL2E, bb.y), fmaf(uf(v[1].z) + uf(v[5].z), SL2E, bb.z), fmaf(uf(v[1].w) + uf(v[5].w), SL2E, bb.w),
                       (uf(hf ? v[2].z : v[2].x) + uf(hf ? v[6].z : v[6].x)) * SL2E, (uf(hf ? v[2].w : v[2].y) + uf(hf ? v[6].w : v[6].y)) * SL2E};
        float mx = fmaxf(fmaxf(fmaxf(fmaxf(e[0], e[1]), fmaxf(e[2], e[3])), fmaxf(fmaxf(e[4], e[5]), fmaxf(e[6], e[7]))), fmaxf(e[8], e[9]));
        mx = fmaxf(mx, __shfl_xor_sync(0xffffffffu, mx, 1));
        mx = fmaxf(mx, __shfl_xor_sync(0xffffffffu, mx, 2));
        const uint32_t vs = t2.z + (a % 3) * 16384, oxs = lds_vol(tb + T4 + 4);
        const uint4 v0 = lds_v4(vs), v1 = lds_v4(vs + 512);
#pragma unroll
        for (int i = 0; i < 10; i++) e[i] = ex2(e[i] - mx);
        float sum = ((e[0] + e[1]) + (e[2] + e[3])) + ((e[4] + e[5]) + (e[6] + e[7])) + (e[8] + e[9]);
        sum += __shfl_xor_sync(0xffffffffu, sum, 1);
        sum += __shfl_xor_sync(0xffffffffu, sum, 2);
        const float inv = rcp(sum);
#pragma unroll
        for (int i = 0; i < 5; i++) sts_u32(t3.z + (i >> 1) * 512 + (i & 1) * 8, pack_bf16(e[2 * i] * inv, e[2 * i + 1] * inv));
        if (wu == 0) asm volatile("cp.async.bulk.wait_group.read 0;" ::: "memory");
        bar_sync(B_P, 128);
        uint4 q[5];
#pragma unroll
        for (int i = 0; i < 5; i++) q[i] = lds_v4(t2.w + (i + (i > 0)) * 512);
        float c[4][4];
        mma16816z(c[2], q[2].x, q[2].y, q[2].z, q[2].w, v0.x, v0.y); mma16816z(c[3], q[2].x, q[2].y, q[2].z, q[2].w, v1.x, v1.y);
        mma16816z(c[0], q[0].x, q[0].y, q[0].z, q[0].w, v0.x, v0.y); mma16816z(c[1], q[0].x, q[0].y, q[0].z, q[0].w, v1.x, v1.y);
        mma16816(c[2], q[3].x, q[3].y, q[3].z, q[3].w, v0.z, v0.w); mma16816(c[3], q[3].x, q[3].y, q[3].z, q[3].w, v1.z, v1.w);
        mma1688(c[0], q[1].x, q[1].y, vm0); mma1688(c[1], q[1].x, q[1].y, vm1);
        mma1688(c[2], q[4].x, q[4].y, vm0); mma1688(c[3], q[4].x, q[4].y, vm1);
#pragma unroll
        for (int m = 0; m < 2; m++)
          asm volatile("stmatrix.sync.aligned.m8n8.x4.shared.b16 [%0], {%1,%2,%3,%4};" ::"r"(oxs + m * 2048), "r"(pack_bf16(c[2 * m][0], c[2 * m][1])), "r"(pack_bf16(c[2 * m][2], c[2 * m][3])),
                       "r"(pack_bf16(c[2 * m + 1][0], c[2 * m + 1][1])), "r"(pack_bf16(c[2 * m + 1][2], c[2 * m + 1][3])) : "memory");
      }
    }
    TSW(19, 0); TSW(20, 4);
    if (s >= 0 && s < NSEG) {
      const uint4 t1 = tab(tb, 1);
      const uint8_t* op = xw + (t1.x + slot) - 2048;
      const uint32_t wo = t1.z;
      uint4 at[4];
#pragma unroll
      for (int i = 0; i < 4; i++) at[i] = lds_v4(wo + i * 512);
      uint8_t* mp = xw + (t1.y + slot);
      const uint32_t tsel = (t1.y & 12) ? 0u : 1u;
      SCHED();
      wait_until(tm);
      TSW(22, 0);
      int nmiss = 0;
      uint4 o[8];
#pragma unroll
      for (int i = 0; i < 8; i++) o[i] = ld_rlx(op + i * 512);
      float acc[2][2][4];
#pragma unroll
      for (int gq = 0; gq < 4; gq++) {
        if (!__all_sync(0xffffffffu, (bad2(o[2 * gq].x, o[2 * gq + 1].x, ph) & 1) == 0)) {
          nmiss |= 1 << gq;
#pragma unroll 1
          for (int it = 0; it < POLL_MAX; it++) {
#pragma unroll
            for (int i = 2 * gq; i < 8; i++) reload(o[i], op + i * 512, ph);
            if (__all_sync(0xffffffffu, (bad2(o[2 * gq].x, o[2 * gq + 1].x, ph) & 1) == 0)) break;
          }
        }
        if (gq == 0) TSW(21, 0);
        if (gq == 3) TSA(8 + (threadIdx.x >> 5));
#pragma unroll
        for (int i = 2 * gq; i < 2 * gq + 2; i++) {
          const int si = (i == 0) ? 0 : (i == 3) ? 1 : (i == 6) ? 2 : -1, ri = i - 1 - (i > 3) - (i > 6);
#pragma unroll
          for (int u = 0; u < 2; u++)
#pragma unroll
            for (int mt = 0; mt < 2; mt++) {
              const uint32_t b0 = u ? o[i].z : o[i].x, b1 = u ? o[i].w : o[i].y;
              if (si < 0) mma16816(acc[mt][u], of[mt][si < 0 ? 2 * ri + u : 0][0], of[mt][si < 0 ? 2 * ri + u : 0][1], of[mt][si < 0 ? 2 * ri + u : 0][2], of[mt][si < 0 ? 2 * ri + u : 0][3], b0, b1);
              else {
                const uint4 a = at[2 * u + mt];
                if (i == 0) mma16816z(acc[mt][u], a.x, a.y, a.z, a.w, b0, b1); else mma16816(acc[mt][u], a.x, a.y, a.z, a.w, b0, b1);
                if (si < 2) at[2 * u + mt] = lds_v4(wo + (4 * (si + 1) + 2 * u + mt) * 512);
              }
            }
        }
      }
#pragma unroll
      for (int mt = 0; mt < 2; mt++)
        sts_f4(wo + V_RED + mt * 512, acc[mt][0][0] + acc[mt][1][0], acc[mt][0][2] + acc[mt][1][2], acc[mt][0][1] + acc[mt][1][1], acc[mt][0][3] + acc[mt][1][3]);
      if constexpr (WG == 1) bar_arrive(B_RED, 256);
      if constexpr (WG == 0) {
        bar_sync(B_RED, 256);
        float2 r[8];
#pragma unroll
        for (int i = 0; i < 8; i++) r[i] = lds_f2(t1.w + i * 16384);
        const uint32_t mw = (pack_bf16(((r[0].x + r[1].x) + (r[2].x + r[3].x)) + ((r[4].x + r[5].x) + (r[6].x + r[7].x)),
                                       ((r[0].y + r[1].y) + (r[2].y + r[3].y)) + ((r[4].y + r[5].y) + (r[6].y + r[7].y))) & ~tsel) | (tsel & ph);
        st_rlx32(mp, mw); st_rlx32(mp + 4096, mw);
      }
      SCHED();
      if (WG == 0) TSA(2 + (threadIdx.x >> 5));
      dop = max(dop + (nmiss ? DLY_UP : -DLY_DN), 0);
      tpub = clk() + dv;
      TSW(23, 0);
    }
    if (WG == 1 && s >= 1) {
      fence_async_smem();
      if (wu == 0) {
        bar_sync(B_OX, 128);
        if ((threadIdx.x & 31) == 0) {
          asm volatile("cp.async.bulk.tensor.2d.global.shared::cta.bulk_group [%0, {%2, %3}], [%1];" ::"l"(tmOx), "r"(sb + V_OX), "r"(h * DH + 64 * j), "r"(a * SEG) : "memory");
          asm volatile("cp.async.bulk.commit_group;" ::: "memory");
        }
        __syncwarp();
      } else bar_arrive(B_OX, 128);
    }
  }
  if (WG == 1) asm volatile("cp.async.bulk.wait_group 0;" ::: "memory");
}

__global__ void __cluster_dims__(2, 1, 1) __launch_bounds__(256, 1)
k1_rec(const __grid_constant__ CUtensorMap tmX, const __grid_constant__ CUtensorMap tmWq, const __grid_constant__ CUtensorMap tmWk,
       const __grid_constant__ CUtensorMap tmWv, const __grid_constant__ CUtensorMap tmWo, const __grid_constant__ CUtensorMap tmOx, uint8_t* __restrict__ xw, const bf16* __restrict__ mem0,
       const bf16* Wq, const bf16* Wk, const bf16* Wv, const bf16* Wo) {
  extern __shared__ __align__(1024) uint8_t smem[];
  const uint32_t sb = smem_u32(smem);
  if ((sb & 0xFFFFFFu) != SMEM0) __trap();
  {
    const int tid = threadIdx.x, wg = tid >> 7, cta = blockIdx.x, h = cta >> 2, j = cta & 1;
    const uint32_t BAR = sb + K1_BAR;
    if (tid == 0) {
      mbar_init(BAR + MB_X, 1); mbar_init(BAR + MB_X + 8, 1); mbar_init(BAR + MB_S, 5);
      for (int i = 0; i < 24; i++) mbar_init(BAR + MB_A + 8 * i, 1);
      asm volatile("fence.mbarrier_init.release.cluster;" ::: "memory");
    }
    __syncthreads();
    TSG(16);
#define WPF 0
    if (WPF && tid >= 64 && tid < 64 + 4 * WPF) {
      const int m = (tid - 64) >> 2;
      const bf16* W = (m == 0) ? Wq : (m == 1) ? Wk : (m == 2) ? Wv : Wo;
      asm volatile("cp.async.bulk.prefetch.L2.global [%0], %1;" ::"l"(W + (size_t)cta * 32768 + (tid & 3) * 8192), "r"(16384) : "memory");
    }
    if ((tid & 127) == 0) {
      const uint32_t pb = BAR + MB_P + wg * 32;
      if (!(cta & 2)) {
        const CUtensorMap* tm = wg ? &tmWk : &tmWq;
        for (int c = 0; c < 2; c++) {
          mbar_expect_tx(pb + 8 * c, 32768);
          for (int t = 0; t < 2; t++) tma_load_2d(sb + Q_STG + wg * 65536 + (2 * c + t) * 16384, tm, h * DH + 64 * t, j * 512 + 128 * c, pb + 8 * c);
        }
        mbar_expect_tx(pb + 24, 32768);
        for (int t = 0; t < 2; t++) tma_load_2d(sb + Q_WRES + wg * 32768 + t * 16384, tm, h * DH + 64 * t, j * 512 + 384, pb + 24);
      } else {
        mbar_expect_tx(pb, 65536);
        for (int c = 0; c < 3; c++) tma_load_2d(sb + V_STG + wg * 65536 + c * 16384, &tmWv, h * DH + 64 * (wg ^ j), j * 512 + 128 * c, pb);
        tma_load_2d(sb + V_WRES + wg * 16384, &tmWv, h * DH + 64 * (wg ^ j), j * 512 + 384, pb);
      }
    }
    __syncwarp();
    if (tid < 32) load_x(sb, (cta & 2) ? V_XT : Q_XT, &tmX, 0, j);
    if (tid == 32) sts_u32(BAR + 240, probe_side(xw, sb));
    __syncwarp();
  }
  const int role = __shfl_sync(0xffffffffu, (threadIdx.x >> 7) | (blockIdx.x & 2), 0);
  if (role == 0) role_q(sb, &tmX, &tmWq, xw);
  else if (role == 1) role_k(sb, &tmWk, xw, mem0);
  else if (role == 2) role_v<0>(sb, &tmX, &tmWo, &tmOx, xw, mem0);
  else role_v<1>(sb, &tmX, &tmWo, &tmOx, xw, mem0);
  asm volatile("griddepcontrol.launch_dependents;" ::: "memory");
  TS_DUMP();
  TSG(29);
}

__global__ void __launch_bounds__(256, 1) kc_conv(const bf16* __restrict__ ssm_k, const bf16* __restrict__ ssm_D) {
  extern __shared__ __align__(1024) uint8_t smem[];
  const uint32_t sb = smem_u32(smem);
  const int tid = threadIdx.x, wg = __shfl_sync(0xffffffffu, tid >> 7, 0), cta = blockIdx.x;
  asm volatile("griddepcontrol.launch_dependents;" ::: "memory");
#pragma unroll 1
  for (int it = 0; it < POLL_MAX; it++) {
    unsigned v; asm volatile("ld.acquire.gpu.global.u32 %0, [%1];" : "=r"(v) : "l"(&g_kvT_ready) : "memory");
    if (v >= 4) break;
  }
  conv_channels<true>(sb + wg * 49152, tid & 127, 1 + wg, 256 * (cta >> 5) + KB_BG + 2 * (cta & 31) + wg, 64,
                      g_one * ((256 - KB_BG - 2 * (cta & 31) - wg + 63) / 64), ssm_k, ssm_D);
  asm volatile("griddepcontrol.wait;" ::: "memory");
}

constexpr int G_STAGES = 5;
constexpr int G_STAGE_BYTES = 32768;
constexpr int G_SMEM = (G_STAGES + 2) * G_STAGE_BYTES + 1024 + 256;

template <int EPI>
__global__ void __launch_bounds__(384, 1)
k2_gemm(const __grid_constant__ CUtensorMap tmA, const __grid_constant__ CUtensorMap tmB, const __grid_constant__ CUtensorMap tmY,
        const __grid_constant__ CUtensorMap tmQ, const __grid_constant__ CUtensorMap tmOut, int kblocks) {
  extern __shared__ uint8_t smem_raw[];
  const uint32_t sb = (smem_u32(smem_raw) + 1023) & ~1023u;
  const uint32_t ysm = sb + G_STAGES * G_STAGE_BYTES;
  const uint32_t qsm = ysm + G_STAGE_BYTES;
  const uint32_t bars = qsm + G_STAGE_BYTES;
  const int tid = threadIdx.x, warp = tid >> 5, lane = tid & 31;
  const int n0 = blockIdx.x * 128, m0 = blockIdx.y * 128;
#define TS2(i)
  TS2(30);
  if (tid == 0) {
    for (int s = 0; s < G_STAGES; s++) { mbar_init(bars + 8 * s, 1); mbar_init(bars + 64 + 8 * s, 2); }
    mbar_init(bars + 128, 1);
    asm volatile("fence.mbarrier_init.release.cluster;" ::: "memory");
  }
  __syncthreads();
  if (warp >= 8) {
    asm volatile("setmaxnreg.dec.sync.aligned.u32 40;\n");
    if (warp == 8 && lane == 0) {
      int st = 0; uint32_t ph = 1;
      mbar_expect_tx(bars + 128, 65536);
      tma_load_2d(qsm, &tmQ, n0, m0, bars + 128);
      tma_load_2d(qsm + 16384, &tmQ, n0 + 64, m0, bars + 128);
      asm volatile("griddepcontrol.wait;" ::: "memory");
      tma_load_2d(ysm, &tmY, m0, n0, bars + 128);
      tma_load_2d(ysm + 16384, &tmY, m0 + 64, n0, bars + 128);
      for (int kb = 0; kb < kblocks; kb++) {
        mbar_wait(bars + 64 + 8 * st, ph);
        const uint32_t dst = sb + st * G_STAGE_BYTES, fb = bars + 8 * st;
        mbar_expect_tx(fb, G_STAGE_BYTES);
        tma_load_2d(dst, &tmA, kb * 64, m0, fb);
        tma_load_2d(dst + 16384, &tmB, n0, kb * 64, fb);
        tma_load_2d(dst + 24576, &tmB, n0 + 64, kb * 64, fb);
        if (++st == G_STAGES) { st = 0; ph ^= 1; }
      }
    } else if (warp > 8) {
      const int cta = blockIdx.y * gridDim.x + blockIdx.x;
      asm volatile("griddepcontrol.wait;" ::: "memory");
      if (cta == 0 && tid == 288) g_kvT_ready = 0;
    }
  } else {
    asm volatile("setmaxnreg.inc.sync.aligned.u32 232;\n");
    asm volatile("griddepcontrol.wait;" ::: "memory");
    const int wg = warp >> 2;
    float acc[64];
    int st = 0; uint32_t ph = 0;
    for (int kb = 0; kb < kblocks; kb++) {
      mbar_wait(bars + 8 * st, ph);
      const uint32_t a = sb + st * G_STAGE_BYTES + wg * 8192, b = sb + st * G_STAGE_BYTES + 16384;
      const uint64_t da = make_desc(a, 16, 1024, 1), db = make_desc(b, 8192, 1024, 1);
      wg_fence();
#pragma unroll
      for (int ks = 0; ks < 4; ks++) wg_ss_n128_tb<0>(acc, da + ks * 2, db + ks * 128, (kb | ks) != 0);
      wg_commit();
      wg_wait<1>();
      if (kb > 0) {
        const int ps = (st == 0) ? G_STAGES - 1 : st - 1;
        if ((tid & 127) == 0) mbar_arrive(bars + 64 + 8 * ps);
      }
      if (++st == G_STAGES) { st = 0; ph ^= 1; }
    }
    wg_wait<0>(); fence_regs(acc);
    TS2(27);
    const int g = lane >> 2;
    const int rl = wg * 64 + (warp & 3) * 16;
    const float gt0 = g_gate[m0 + rl + g], gt1 = g_gate[m0 + rl + g + 8];
    const float om0 = rbf(1.f - gt0), om1 = rbf(1.f - gt1);
    mbar_wait(bars + 128, 0);
    const int mi = lane >> 3, tc = wg * 8 + (warp & 3) * 2 + (mi & 1);
    const int qr = rl + 8 * (mi & 1) + (lane & 7);
#pragma unroll
    for (int j2 = 0; j2 < 8; j2++) {
      const int d = 16 * j2 + 8 * (mi >> 1) + (lane & 7);
      uint32_t yf[4], qf[4], of[4];
      asm volatile("ldmatrix.sync.aligned.m8n8.x4.trans.shared.b16 {%0,%1,%2,%3}, [%4];" : "=r"(yf[0]), "=r"(yf[1]), "=r"(yf[2]), "=r"(yf[3])
                   : "r"(ysm + (tc >> 3) * 16384 + d * 128 + (((tc & 7) ^ (d & 7)) << 4)) : "memory");
      const int cc = 2 * j2 + (mi >> 1);
      const uint32_t qa = qsm + (cc >> 3) * 16384 + qr * 128 + (((cc & 7) ^ (qr & 7)) << 4);
      asm volatile("ldmatrix.sync.aligned.m8n8.x4.shared.b16 {%0,%1,%2,%3}, [%4];" : "=r"(qf[0]), "=r"(qf[1]), "=r"(qf[2]), "=r"(qf[3]) : "r"(qa) : "memory");
#pragma unroll
      for (int jj = 0; jj < 2; jj++)
#pragma unroll
        for (int hf = 0; hf < 2; hf++) {
          const int j = 2 * j2 + jj;
          const float gt = hf ? gt1 : gt0, om = hf ? om1 : om0;
          const uint32_t aw = bmul2(qf[2 * jj + hf], yf[2 * jj + hf]);
          const uint32_t bw = pack_bf16(acc[4 * j + 2 * hf], acc[4 * j + 2 * hf + 1]);
          of[2 * jj + hf] = badd2(pack_bf16(gt * bf_lo(aw), gt * bf_hi(aw)), pack_bf16(om * bf_lo(bw), om * bf_hi(bw)));
        }
      asm volatile("stmatrix.sync.aligned.m8n8.x4.shared.b16 [%0], {%1,%2,%3,%4};" ::"r"(qa), "r"(of[0]), "r"(of[1]), "r"(of[2]), "r"(of[3]) : "memory");
    }
    fence_async_smem();
    bar_sync(1, 256);
    if (tid == 0) {
      asm volatile("cp.async.bulk.tensor.2d.global.shared::cta.bulk_group [%0, {%2, %3}], [%1];" ::"l"(&tmOut), "r"(qsm), "r"(n0), "r"(m0) : "memory");
      asm volatile("cp.async.bulk.tensor.2d.global.shared::cta.bulk_group [%0, {%2, %3}], [%1];" ::"l"(&tmOut), "r"(qsm + 16384), "r"(n0 + 64), "r"(m0) : "memory");
      asm volatile("cp.async.bulk.commit_group;\ncp.async.bulk.wait_group 0;" ::: "memory");
    }
    TS2(31);
  }
}

typedef CUresult (*PFN_encodeTiled)(CUtensorMap*, CUtensorMapDataType, cuuint32_t, void*, const cuuint64_t*, const cuuint64_t*,
                                    const cuuint32_t*, const cuuint32_t*, CUtensorMapInterleave, CUtensorMapSwizzle,
                                    CUtensorMapL2promotion, CUtensorMapFloatOOBfill);
static PFN_encodeTiled get_encode() {
  static PFN_encodeTiled fn = nullptr;
  if (!fn) {
    void* p = nullptr; cudaDriverEntryPointQueryResult st;
    cudaGetDriverEntryPoint("cuTensorMapEncodeTiled", &p, cudaEnableDefault, &st);
    fn = (PFN_encodeTiled)p;
  }
  return fn;
}
static CUtensorMap make_tm(const void* ptr, uint64_t rows, uint64_t cols, uint32_t brows, uint32_t bcols, bool swz = true) {
  CUtensorMap tm;
  cuuint64_t dims[2] = {cols, rows};
  cuuint64_t strides[1] = {cols * 2};
  cuuint32_t box[2] = {bcols, brows};
  cuuint32_t es[2] = {1, 1};
  get_encode()(&tm, CU_TENSOR_MAP_DATA_TYPE_BFLOAT16, 2, const_cast<void*>(ptr), dims, strides, box, es, CU_TENSOR_MAP_INTERLEAVE_NONE,
               swz ? CU_TENSOR_MAP_SWIZZLE_128B : CU_TENSOR_MAP_SWIZZLE_NONE, CU_TENSOR_MAP_L2_PROMOTION_L2_256B, CU_TENSOR_MAP_FLOAT_OOB_FILL_NONE);
  return tm;
}
static CUtensorMap make_tm_x(const void* ptr) {
  CUtensorMap tm;
  cuuint64_t dims[3] = {64, (cuuint64_t)SEQ, 16};
  cuuint64_t strides[2] = {DM * 2, 128};
  cuuint32_t box[3] = {64, SEG, 8};
  cuuint32_t es[3] = {1, 1, 1};
  get_encode()(&tm, CU_TENSOR_MAP_DATA_TYPE_BFLOAT16, 3, const_cast<void*>(ptr), dims, strides, box, es, CU_TENSOR_MAP_INTERLEAVE_NONE,
               CU_TENSOR_MAP_SWIZZLE_128B, CU_TENSOR_MAP_L2_PROMOTION_L2_256B, CU_TENSOR_MAP_FLOAT_OOB_FILL_NONE);
  return tm;
}
template <typename T> static T* sym_addr(T& sym) { void* p = nullptr; cudaGetSymbolAddress(&p, sym); return (T*)p; }

#define RUN(bit) true

#define K2_PDL 1
extern "C" void kernel_launch(void* const* d_in, const int* in_sizes, int n_in, void* d_out, int out_size) {
  const bf16* q = (const bf16*)d_in[0];
  const bf16* k = (const bf16*)d_in[1];
  const bf16* v = (const bf16*)d_in[2];
  const bf16* shift_k = (const bf16*)d_in[3];
  const bf16* ssm_k = (const bf16*)d_in[4];
  const bf16* ssm_D = (const bf16*)d_in[5];
  const bf16* mem0 = (const bf16*)d_in[7];
  const bf16* Wq = (const bf16*)d_in[8];
  const bf16* Wk = (const bf16*)d_in[9];
  const bf16* Wv = (const bf16*)d_in[10];
  const bf16* Wo = (const bf16*)d_in[11];
  const bf16* gate_w = (const bf16*)d_in[13];
  bf16* out = (bf16*)d_out;
  cudaStream_t st = cudaStreamPerThread;
  static cudaStream_t st2 = nullptr;
  static cudaEvent_t ev0 = nullptr, ev1 = nullptr;
  if (!st2) {
    cudaStreamCreateWithFlags(&st2, cudaStreamNonBlocking);
    cudaEventCreateWithFlags(&ev0, cudaEventDisableTiming);
    cudaEventCreateWithFlags(&ev1, cudaEventDisableTiming);
    cudaFuncSetAttribute(kb_conv, cudaFuncAttributeMaxDynamicSharedMemorySize, KB_SMEM);
    cudaFuncSetAttribute(kc_conv, cudaFuncAttributeMaxDynamicSharedMemorySize, 200 * 1024);
    cudaFuncSetAttribute(k1_rec, cudaFuncAttributeMaxDynamicSharedMemorySize, K1_SMEM);
    cudaFuncSetAttribute(k2_gemm<1>, cudaFuncAttributeMaxDynamicSharedMemorySize, G_SMEM);
  }
  void* ox = nullptr; cudaGetSymbolAddress(&ox, g_ox);
  void* y2 = nullptr; cudaGetSymbolAddress(&y2, g_y2T);
  CUtensorMap tmO = make_tm(ox, SEQ, HD, 128, 64);
  CUtensorMap tmWo = make_tm(Wo, HD, DM, 64, 64);
  CUtensorMap tmX = make_tm_x(q);
  CUtensorMap tmY = make_tm(y2, DM, SEQ, 128, 64);
  CUtensorMap tmQ = make_tm(q, SEQ, DM, 128, 64);
  CUtensorMap tmOut = make_tm(out, SEQ, DM, 128, 64);
  CUtensorMap tmWq = make_tm(Wq, DM, HD, 128, 64), tmWk = make_tm(Wk, DM, HD, 128, 64), tmWv = make_tm(Wv, DM, HD, 128, 64);
  CUtensorMap tmWo1 = make_tm(Wo, HD, DM, 256, 32, false);
  CUtensorMap tmOx = make_tm(ox, SEQ, HD, 32, 64);
  void* xw = nullptr; cudaGetSymbolAddress(&xw, g_xw);
  xw = (void*)(((uintptr_t)xw + (2u << 20) - 1) & ~(uintptr_t)((2u << 20) - 1));
  cudaEventRecord(ev0, st);
  cudaStreamWaitEvent(st2, ev0, 0);
  if (RUN(1)) kb_conv<<<4, 512, KB_SMEM, st2>>>(q, gate_w, k, v, shift_k, ssm_k, ssm_D);
  if (RUN(4)) k1_rec<<<128, 256, K1_SMEM, st>>>(tmX, tmWq, tmWk, tmWv, tmWo1, tmOx, (uint8_t*)xw, mem0, Wq, Wk, Wv, Wo);
  if (RUN(2)) {
    cudaLaunchConfig_t cfg = {};
    cfg.gridDim = dim3(128); cfg.blockDim = dim3(256); cfg.dynamicSmemBytes = 200 * 1024; cfg.stream = st;
    cudaLaunchAttribute at[1];
    at[0].id = cudaLaunchAttributeProgrammaticStreamSerialization; at[0].val.programmaticStreamSerializationAllowed = 1;
    cfg.attrs = at; cfg.numAttrs = 1;
    cudaLaunchKernelEx(&cfg, kc_conv, ssm_k, ssm_D);
  }
  cudaEventRecord(ev1, st2);
  cudaStreamWaitEvent(st, ev1, 0);
  if (RUN(8)) {
    cudaLaunchConfig_t cfg = {};
    cfg.gridDim = dim3(DM / 128, SEQ / 128); cfg.blockDim = dim3(384); cfg.dynamicSmemBytes = G_SMEM; cfg.stream = st;
    cudaLaunchAttribute at[1];
    at[0].id = cudaLaunchAttributeProgrammaticStreamSerialization; at[0].val.programmaticStreamSerializationAllowed = K2_PDL;
    cfg.attrs = at; cfg.numAttrs = 1;
    cudaLaunchKernelEx(&cfg, k2_gemm<1>, tmO, tmWo, tmY, tmQ, tmOut, HD / 64);
  }
}
```

```cpp
#include <cuda_runtime.h>
#include <cuda_bf16.h>
#include <cuda.h>
#include <stdint.h>
#include <string.h>

typedef __nv_bfloat16 bf16;

constexpr int SEQ = 2048, DM = 1024, NH = 32, DH = 128, HD = NH * DH, MEM = 8, SEG = 32, NSEG = SEQ / SEG;

__device__ __forceinline__ uint32_t smem_u32(const void* p) { return (uint32_t)__cvta_generic_to_shared(p); }
__device__ __forceinline__ void wg_fence() { asm volatile("wgmma.fence.sync.aligned;\n" ::: "memory"); }
__device__ __forceinline__ void wg_commit() { asm volatile("wgmma.commit_group.sync.aligned;\n" ::: "memory"); }
template <int N> __device__ __forceinline__ void wg_wait() { asm volatile("wgmma.wait_group.sync.aligned %0;\n" ::"n"(N) : "memory"); }
template <int N> __device__ __forceinline__ void fence_regs(float (&a)[N]) {
#pragma unroll
  for (int i = 0; i < N; i++) asm volatile("" : "+f"(a[i])::"memory");
}
__device__ __forceinline__ void fence_async_smem() { asm volatile("fence.proxy.async.shared::cta;\n" ::: "memory"); }
__device__ __forceinline__ void bar_sync(int id, int n) { asm volatile("bar.sync %0, %1;" ::"r"(id), "r"(n) : "memory"); }
__device__ __forceinline__ void bar_arrive(int id, int n) { asm volatile("bar.arrive %0, %1;" ::"r"(id), "r"(n) : "memory"); }
__device__ __forceinline__ uint64_t make_desc(uint32_t addr, uint32_t lbo, uint32_t sbo, uint32_t swz) {
  return (uint64_t)((addr & 0x3FFFF) >> 4) | ((uint64_t)((lbo & 0x3FFFF) >> 4) << 16) | ((uint64_t)((sbo & 0x3FFFF) >> 4) << 32) | ((uint64_t)swz << 62);
}
__device__ __forceinline__ void mbar_init(uint32_t bar, int cnt) { asm volatile("mbarrier.init.shared::cta.b64 [%0], %1;" ::"r"(bar), "r"(cnt) : "memory"); }
__device__ __forceinline__ void mbar_expect_tx(uint32_t bar, uint32_t bytes) {
  asm volatile("mbarrier.arrive.expect_tx.shared::cta.b64 _, [%0], %1;" ::"r"(bar), "r"(bytes) : "memory");
}
__device__ __forceinline__ void mbar_arrive(uint32_t bar) { asm volatile("mbarrier.arrive.shared::cta.b64 _, [%0];" ::"r"(bar) : "memory"); }
__device__ __forceinline__ bool mbar_try(uint32_t bar, uint32_t parity) {
  uint32_t ok;
  asm volatile("{\n.reg .pred p;\nmbarrier.try_wait.parity.shared::cta.b64 p, [%1], %2;\nselp.u32 %0, 1, 0, p;\n}" : "=r"(ok) : "r"(bar), "r"(parity) : "memory");
  return ok != 0;
}
__device__ __forceinline__ void mbar_wait(uint32_t bar, uint32_t parity) {
  for (int i = 0; i < (1 << 22); i++) if (mbar_try(bar, parity)) return;
}
__device__ __forceinline__ void tma_load_2d(uint32_t dst, const CUtensorMap* tm, int c0, int c1, uint32_t bar) {
  asm volatile("cp.async.bulk.tensor.2d.shared::cluster.global.mbarrier::complete_tx::bytes [%0], [%1, {%3, %4}], [%2];"
               ::"r"(dst), "l"(tm), "r"(bar), "r"(c0), "r"(c1) : "memory");
}
__device__ __forceinline__ void tma_load_2d_mc(uint32_t dst, const CUtensorMap* tm, int c0, int c1, uint32_t bar, uint16_t mask) {
  asm volatile("cp.async.bulk.tensor.2d.shared::cluster.global.mbarrier::complete_tx::bytes.multicast::cluster [%0], [%1, {%3, %4}], [%2], %5;"
               ::"r"(dst), "l"(tm), "r"(bar), "r"(c0), "r"(c1), "h"(mask) : "memory");
}
__device__ __forceinline__ uint32_t pack_bf16(float lo, float hi) {
  uint32_t r; asm("cvt.rn.bf16x2.f32 %0, %1, %2;" : "=r"(r) : "f"(hi), "f"(lo)); return r;
}
__device__ __forceinline__ float bf_lo(uint32_t w) { return __uint_as_float(w << 16); }
__device__ __forceinline__ float bf_hi(uint32_t w) { return __uint_as_float(w & 0xffff0000u); }
__device__ __forceinline__ float rbf(float x) { return __bfloat162float(__float2bfloat16_rn(x)); }
__device__ __forceinline__ uint32_t prmt(uint32_t a, uint32_t b, uint32_t sel) { uint32_t r; asm("prmt.b32 %0, %1, %2, %3;" : "=r"(r) : "r"(a), "r"(b), "r"(sel)); return r; }
__device__ __forceinline__ uint4 ldg_nc_v4(const void* p) {
  uint4 v; asm volatile("ld.global.nc.L1::no_allocate.v4.u32 {%0,%1,%2,%3}, [%4];" : "=r"(v.x), "=r"(v.y), "=r"(v.z), "=r"(v.w) : "l"(p)); return v;
}
__device__ __forceinline__ void sts_v4(uint32_t a, uint4 v) { asm volatile("st.shared.v4.u32 [%0], {%1,%2,%3,%4};" ::"r"(a), "r"(v.x), "r"(v.y), "r"(v.z), "r"(v.w) : "memory"); }
__device__ __forceinline__ uint4 lds_v4(uint32_t a) { uint4 v; asm volatile("ld.shared.v4.u32 {%0,%1,%2,%3}, [%4];" : "=r"(v.x), "=r"(v.y), "=r"(v.z), "=r"(v.w) : "r"(a) : "memory"); return v; }
__device__ __forceinline__ uint32_t lds_u32(uint32_t a) { uint32_t v; asm volatile("ld.shared.u32 %0, [%1];" : "=r"(v) : "r"(a) : "memory"); return v; }
__device__ __forceinline__ void sts_u32(uint32_t a, uint32_t v) { asm volatile("st.shared.u32 [%0], %1;" ::"r"(a), "r"(v) : "memory"); }

template<int OFF, int NT> __device__ __forceinline__ void wg_rs_n8(float (&d)[NT], uint32_t a0, uint32_t a1, uint32_t a2, uint32_t a3, uint64_t db, int sd) {
  asm volatile("{\n.reg .pred p;\nsetp.ne.b32 p, %9, 0;\n"
    "wgmma.mma_async.sync.aligned.m64n8k16.f32.bf16.bf16 {%0, %1, %2, %3}, {%4, %5, %6, %7}, %8, p, 1, 1, 0;\n}\n"
    : "+f"(d[OFF + 0]), "+f"(d[OFF + 1]), "+f"(d[OFF + 2]), "+f"(d[OFF + 3]) : "r"(a0), "r"(a1), "r"(a2), "r"(a3), "l"(db), "r"(sd));
}
template<int OFF, int NT> __device__ __forceinline__ void wg_rs_n16(float (&d)[NT], uint32_t a0, uint32_t a1, uint32_t a2, uint32_t a3, uint64_t db, int sd) {
  asm volatile("{\n.reg .pred p;\nsetp.ne.b32 p, %13, 0;\n"
    "wgmma.mma_async.sync.aligned.m64n16k16.f32.bf16.bf16 {%0, %1, %2, %3, %4, %5, %6, %7}, {%8, %9, %10, %11}, %12, p, 1, 1, 0;\n}\n"
    : "+f"(d[OFF + 0]), "+f"(d[OFF + 1]), "+f"(d[OFF + 2]), "+f"(d[OFF + 3]), "+f"(d[OFF + 4]), "+f"(d[OFF + 5]), "+f"(d[OFF + 6]), "+f"(d[OFF + 7]) : "r"(a0), "r"(a1), "r"(a2), "r"(a3), "l"(db), "r"(sd));
}
template<int OFF, int NT> __device__ __forceinline__ void wg_rs_n24(float (&d)[NT], uint32_t a0, uint32_t a1, uint32_t a2, uint32_t a3, uint64_t db, int sd) {
  asm volatile("{\n.reg .pred p;\nsetp.ne.b32 p, %17, 0;\n"
    "wgmma.mma_async.sync.aligned.m64n24k16.f32.bf16.bf16 {%0, %1, %2, %3, %4, %5, %6, %7, %8, %9, %10, %11}, {%12, %13, %14, %15}, %16, p, 1, 1, 0;\n}\n"
    : "+f"(d[OFF + 0]), "+f"(d[OFF + 1]), "+f"(d[OFF + 2]), "+f"(d[OFF + 3]), "+f"(d[OFF + 4]), "+f"(d[OFF + 5]), "+f"(d[OFF + 6]), "+f"(d[OFF + 7]), "+f"(d[OFF + 8]), "+f"(d[OFF + 9]), "+f"(d[OFF + 10]), "+f"(d[OFF + 11]) : "r"(a0), "r"(a1), "r"(a2), "r"(a3), "l"(db), "r"(sd));
}
template<int OFF, int NT> __device__ __forceinline__ void wg_rs_n32(float (&d)[NT], uint32_t a0, uint32_t a1, uint32_t a2, uint32_t a3, uint64_t db, int sd) {
  asm volatile("{\n.reg .pred p;\nsetp.ne.b32 p, %21, 0;\n"
    "wgmma.mma_async.sync.aligned.m64n32k16.f32.bf16.bf16 {%0, %1, %2, %3, %4, %5, %6, %7, %8, %9, %10, %11, %12, %13, %14, %15}, {%16, %17, %18, %19}, %20, p, 1, 1, 0;\n}\n"
    : "+f"(d[OFF + 0]), "+f"(d[OFF + 1]), "+f"(d[OFF + 2]), "+f"(d[OFF + 3]), "+f"(d[OFF + 4]), "+f"(d[OFF + 5]), "+f"(d[OFF + 6]), "+f"(d[OFF + 7]), "+f"(d[OFF + 8]), "+f"(d[OFF + 9]), "+f"(d[OFF + 10]), "+f"(d[OFF + 11]), "+f"(d[OFF + 12]), "+f"(d[OFF + 13]), "+f"(d[OFF + 14]), "+f"(d[OFF + 15]) : "r"(a0), "r"(a1), "r"(a2), "r"(a3), "l"(db), "r"(sd));
}
template<int OFF, int NT> __device__ __forceinline__ void wg_rs_n40(float (&d)[NT], uint32_t a0, uint32_t a1, uint32_t a2, uint32_t a3, uint64_t db, int sd) {
  asm volatile("{\n.reg .pred p;\nsetp.ne.b32 p, %25, 0;\n"
    "wgmma.mma_async.sync.aligned.m64n40k16.f32.bf16.bf16 {%0, %1, %2, %3, %4, %5, %6, %7, %8, %9, %10, %11, %12, %13, %14, %15, %16, %17, %18, %19}, {%20, %21, %22, %23}, %24, p, 1, 1, 0;\n}\n"
    : "+f"(d[OFF + 0]), "+f"(d[OFF + 1]), "+f"(d[OFF + 2]), "+f"(d[OFF + 3]), "+f"(d[OFF + 4]), "+f"(d[OFF + 5]), "+f"(d[OFF + 6]), "+f"(d[OFF + 7]), "+f"(d[OFF + 8]), "+f"(d[OFF + 9]), "+f"(d[OFF + 10]), "+f"(d[OFF + 11]), "+f"(d[OFF + 12]), "+f"(d[OFF + 13]), "+f"(d[OFF + 14]), "+f"(d[OFF + 15]), "+f"(d[OFF + 16]), "+f"(d[OFF + 17]), "+f"(d[OFF + 18]), "+f"(d[OFF + 19]) : "r"(a0), "r"(a1), "r"(a2), "r"(a3), "l"(db), "r"(sd));
}
template<int OFF, int NT> __device__ __forceinline__ void wg_rs_n48(float (&d)[NT], uint32_t a0, uint32_t a1, uint32_t a2, uint32_t a3, uint64_t db, int sd) {
  asm volatile("{\n.reg .pred p;\nsetp.ne.b32 p, %29, 0;\n"
    "wgmma.mma_async.sync.aligned.m64n48k16.f32.bf16.bf16 {%0, %1, %2, %3, %4, %5, %6, %7, %8, %9, %10, %11, %12, %13, %14, %15, %16, %17, %18, %19, %20, %21, %22, %23}, {%24, %25, %26, %27}, %28, p, 1, 1, 0;\n}\n"
    : "+f"(d[OFF + 0]), "+f"(d[OFF + 1]), "+f"(d[OFF + 2]), "+f"(d[OFF + 3]), "+f"(d[OFF + 4]), "+f"(d[OFF + 5]), "+f"(d[OFF + 6]), "+f"(d[OFF + 7]), "+f"(d[OFF + 8]), "+f"(d[OFF + 9]), "+f"(d[OFF + 10]), "+f"(d[OFF + 11]), "+f"(d[OFF + 12]), "+f"(d[OFF + 13]), "+f"(d[OFF + 14]), "+f"(d[OFF + 15]), "+f"(d[OFF + 16]), "+f"(d[OFF + 17]), "+f"(d[OFF + 18]), "+f"(d[OFF + 19]), "+f"(d[OFF + 20]), "+f"(d[OFF + 21]), "+f"(d[OFF + 22]), "+f"(d[OFF + 23]) : "r"(a0), "r"(a1), "r"(a2), "r"(a3), "l"(db), "r"(sd));
}
template<int OFF, int NT> __device__ __forceinline__ void wg_rs_n56(float (&d)[NT], uint32_t a0, uint32_t a1, uint32_t a2, uint32_t a3, uint64_t db, int sd) {
  asm volatile("{\n.reg .pred p;\nsetp.ne.b32 p, %33, 0;\n"
    "wgmma.mma_async.sync.aligned.m64n56k16.f32.bf16.bf16 {%0, %1, %2, %3, %4, %5, %6, %7, %8, %9, %10, %11, %12, %13, %14, %15, %16, %17, %18, %19, %20, %21, %22, %23, %24, %25, %26, %27}, {%28, %29, %30, %31}, %32, p, 1, 1, 0;\n}\n"
    : "+f"(d[OFF + 0]), "+f"(d[OFF + 1]), "+f"(d[OFF + 2]), "+f"(d[OFF + 3]), "+f"(d[OFF + 4]), "+f"(d[OFF + 5]), "+f"(d[OFF + 6]), "+f"(d[OFF + 7]), "+f"(d[OFF + 8]), "+f"(d[OFF + 9]), "+f"(d[OFF + 10]), "+f"(d[OFF + 11]), "+f"(d[OFF + 12]), "+f"(d[OFF + 13]), "+f"(d[OFF + 14]), "+f"(d[OFF + 15]), "+f"(d[OFF + 16]), "+f"(d[OFF + 17]), "+f"(d[OFF + 18]), "+f"(d[OFF + 19]), "+f"(d[OFF + 20]), "+f"(d[OFF + 21]), "+f"(d[OFF + 22]), "+f"(d[OFF + 23]), "+f"(d[OFF + 24]), "+f"(d[OFF + 25]), "+f"(d[OFF + 26]), "+f"(d[OFF + 27]) : "r"(a0), "r"(a1), "r"(a2), "r"(a3), "l"(db), "r"(sd));
}
template<int OFF, int NT> __device__ __forceinline__ void wg_rs_n64(float (&d)[NT], uint32_t a0, uint32_t a1, uint32_t a2, uint32_t a3, uint64_t db, int sd) {
  asm volatile("{\n.reg .pred p;\nsetp.ne.b32 p, %37, 0;\n"
    "wgmma.mma_async.sync.aligned.m64n64k16.f32.bf16.bf16 {%0, %1, %2, %3, %4, %5, %6, %7, %8, %9, %10, %11, %12, %13, %14, %15, %16, %17, %18, %19, %20, %21, %22, %23, %24, %25, %26, %27, %28, %29, %30, %31}, {%32, %33, %34, %35}, %36, p, 1, 1, 0;\n}\n"
    : "+f"(d[OFF + 0]), "+f"(d[OFF + 1]), "+f"(d[OFF + 2]), "+f"(d[OFF + 3]), "+f"(d[OFF + 4]), "+f"(d[OFF + 5]), "+f"(d[OFF + 6]), "+f"(d[OFF + 7]), "+f"(d[OFF + 8]), "+f"(d[OFF + 9]), "+f"(d[OFF + 10]), "+f"(d[OFF + 11]), "+f"(d[OFF + 12]), "+f"(d[OFF + 13]), "+f"(d[OFF + 14]), "+f"(d[OFF + 15]), "+f"(d[OFF + 16]), "+f"(d[OFF + 17]), "+f"(d[OFF + 18]), "+f"(d[OFF + 19]), "+f"(d[OFF + 20]), "+f"(d[OFF + 21]), "+f"(d[OFF + 22]), "+f"(d[OFF + 23]), "+f"(d[OFF + 24]), "+f"(d[OFF + 25]), "+f"(d[OFF + 26]), "+f"(d[OFF + 27]), "+f"(d[OFF + 28]), "+f"(d[OFF + 29]), "+f"(d[OFF + 30]), "+f"(d[OFF + 31]) : "r"(a0), "r"(a1), "r"(a2), "r"(a3), "l"(db), "r"(sd));
}
template<int OFF, int NT> __device__ __forceinline__ void wg_rs_n8_tb(float (&d)[NT], uint32_t a0, uint32_t a1, uint32_t a2, uint32_t a3, uint64_t db, int sd) {
  asm volatile("{\n.reg .pred p;\nsetp.ne.b32 p, %9, 0;\n"
    "wgmma.mma_async.sync.aligned.m64n8k16.f32.bf16.bf16 {%0, %1, %2, %3}, {%4, %5, %6, %7}, %8, p, 1, 1, 1;\n}\n"
    : "+f"(d[OFF + 0]), "+f"(d[OFF + 1]), "+f"(d[OFF + 2]), "+f"(d[OFF + 3]) : "r"(a0), "r"(a1), "r"(a2), "r"(a3), "l"(db), "r"(sd));
}
template<int OFF, int NT> __device__ __forceinline__ void wg_rs_n16_tb(float (&d)[NT], uint32_t a0, uint32_t a1, uint32_t a2, uint32_t a3, uint64_t db, int sd) {
  asm volatile("{\n.reg .pred p;\nsetp.ne.b32 p, %13, 0;\n"
    "wgmma.mma_async.sync.aligned.m64n16k16.f32.bf16.bf16 {%0, %1, %2, %3, %4, %5, %6, %7}, {%8, %9, %10, %11}, %12, p, 1, 1, 1;\n}\n"
    : "+f"(d[OFF + 0]), "+f"(d[OFF + 1]), "+f"(d[OFF + 2]), "+f"(d[OFF + 3]), "+f"(d[OFF + 4]), "+f"(d[OFF + 5]), "+f"(d[OFF + 6]), "+f"(d[OFF + 7]) : "r"(a0), "r"(a1), "r"(a2), "r"(a3), "l"(db), "r"(sd));
}
template<int OFF, int NT> __device__ __forceinline__ void wg_ss_n16_ta_tb(float (&d)[NT], uint64_t da, uint64_t db, int sd) {
  asm volatile("{\n.reg .pred p;\nsetp.ne.b32 p, %10, 0;\n"
    "wgmma.mma_async.sync.aligned.m64n16k16.f32.bf16.bf16 {%0, %1, %2, %3, %4, %5, %6, %7}, %8, %9, p, 1, 1, 1, 1;\n}\n"
    : "+f"(d[OFF + 0]), "+f"(d[OFF + 1]), "+f"(d[OFF + 2]), "+f"(d[OFF + 3]), "+f"(d[OFF + 4]), "+f"(d[OFF + 5]), "+f"(d[OFF + 6]), "+f"(d[OFF + 7]) : "l"(da), "l"(db), "r"(sd));
}
template<int OFF, int NT> __device__ __forceinline__ void wg_ss_n64_ta(float (&d)[NT], uint64_t da, uint64_t db, int sd) {
  asm volatile("{\n.reg .pred p;\nsetp.ne.b32 p, %34, 0;\n"
    "wgmma.mma_async.sync.aligned.m64n64k16.f32.bf16.bf16 {%0, %1, %2, %3, %4, %5, %6, %7, %8, %9, %10, %11, %12, %13, %14, %15, %16, %17, %18, %19, %20, %21, %22, %23, %24, %25, %26, %27, %28, %29, %30, %31}, %32, %33, p, 1, 1, 1, 0;\n}\n"
    : "+f"(d[OFF + 0]), "+f"(d[OFF + 1]), "+f"(d[OFF + 2]), "+f"(d[OFF + 3]), "+f"(d[OFF + 4]), "+f"(d[OFF + 5]), "+f"(d[OFF + 6]), "+f"(d[OFF + 7]), "+f"(d[OFF + 8]), "+f"(d[OFF + 9]), "+f"(d[OFF + 10]), "+f"(d[OFF + 11]), "+f"(d[OFF + 12]), "+f"(d[OFF + 13]), "+f"(d[OFF + 14]), "+f"(d[OFF + 15]), "+f"(d[OFF + 16]), "+f"(d[OFF + 17]), "+f"(d[OFF + 18]), "+f"(d[OFF + 19]), "+f"(d[OFF + 20]), "+f"(d[OFF + 21]), "+f"(d[OFF + 22]), "+f"(d[OFF + 23]), "+f"(d[OFF + 24]), "+f"(d[OFF + 25]), "+f"(d[OFF + 26]), "+f"(d[OFF + 27]), "+f"(d[OFF + 28]), "+f"(d[OFF + 29]), "+f"(d[OFF + 30]), "+f"(d[OFF + 31]) : "l"(da), "l"(db), "r"(sd));
}
template<int OFF, int NT> __device__ __forceinline__ void wg_ss_n8_ta(float (&d)[NT], uint64_t da, uint64_t db, int sd) {
  asm volatile("{\n.reg .pred p;\nsetp.ne.b32 p, %6, 0;\n"
    "wgmma.mma_async.sync.aligned.m64n8k16.f32.bf16.bf16 {%0, %1, %2, %3}, %4, %5, p, 1, 1, 1, 0;\n}\n"
    : "+f"(d[OFF + 0]), "+f"(d[OFF + 1]), "+f"(d[OFF + 2]), "+f"(d[OFF + 3]) : "l"(da), "l"(db), "r"(sd));
}
template<int OFF, int NT> __device__ __forceinline__ void wg_ss_n128_tb(float (&d)[NT], uint64_t da, uint64_t db, int sd) {
  asm volatile("{\n.reg .pred p;\nsetp.ne.b32 p, %66, 0;\n"
    "wgmma.mma_async.sync.aligned.m64n128k16.f32.bf16.bf16 {%0, %1, %2, %3, %4, %5, %6, %7, %8, %9, %10, %11, %12, %13, %14, %15, %16, %17, %18, %19, %20, %21, %22, %23, %24, %25, %26, %27, %28, %29, %30, %31, %32, %33, %34, %35, %36, %37, %38, %39, %40, %41, %42, %43, %44, %45, %46, %47, %48, %49, %50, %51, %52, %53, %54, %55, %56, %57, %58, %59, %60, %61, %62, %63}, %64, %65, p, 1, 1, 0, 1;\n}\n"
    : "+f"(d[OFF + 0]), "+f"(d[OFF + 1]), "+f"(d[OFF + 2]), "+f"(d[OFF + 3]), "+f"(d[OFF + 4]), "+f"(d[OFF + 5]), "+f"(d[OFF + 6]), "+f"(d[OFF + 7]), "+f"(d[OFF + 8]), "+f"(d[OFF + 9]), "+f"(d[OFF + 10]), "+f"(d[OFF + 11]), "+f"(d[OFF + 12]), "+f"(d[OFF + 13]), "+f"(d[OFF + 14]), "+f"(d[OFF + 15]), "+f"(d[OFF + 16]), "+f"(d[OFF + 17]), "+f"(d[OFF + 18]), "+f"(d[OFF + 19]), "+f"(d[OFF + 20]), "+f"(d[OFF + 21]), "+f"(d[OFF + 22]), "+f"(d[OFF + 23]), "+f"(d[OFF + 24]), "+f"(d[OFF + 25]), "+f"(d[OFF + 26]), "+f"(d[OFF + 27]), "+f"(d[OFF + 28]), "+f"(d[OFF + 29]), "+f"(d[OFF + 30]), "+f"(d[OFF + 31]), "+f"(d[OFF + 32]), "+f"(d[OFF + 33]), "+f"(d[OFF + 34]), "+f"(d[OFF + 35]), "+f"(d[OFF + 36]), "+f"(d[OFF + 37]), "+f"(d[OFF + 38]), "+f"(d[OFF + 39]), "+f"(d[OFF + 40]), "+f"(d[OFF + 41]), "+f"(d[OFF + 42]), "+f"(d[OFF + 43]), "+f"(d[OFF + 44]), "+f"(d[OFF + 45]), "+f"(d[OFF + 46]), "+f"(d[OFF + 47]), "+f"(d[OFF + 48]), "+f"(d[OFF + 49]), "+f"(d[OFF + 50]), "+f"(d[OFF + 51]), "+f"(d[OFF + 52]), "+f"(d[OFF + 53]), "+f"(d[OFF + 54]), "+f"(d[OFF + 55]), "+f"(d[OFF + 56]), "+f"(d[OFF + 57]), "+f"(d[OFF + 58]), "+f"(d[OFF + 59]), "+f"(d[OFF + 60]), "+f"(d[OFF + 61]), "+f"(d[OFF + 62]), "+f"(d[OFF + 63]) : "l"(da), "l"(db), "r"(sd));
}
template<int OFF, int NT> __device__ __forceinline__ void wg_ss_n8_ta_tb(float (&d)[NT], uint64_t da, uint64_t db, int sd) {
  asm volatile("{\n.reg .pred p;\nsetp.ne.b32 p, %6, 0;\n"
    "wgmma.mma_async.sync.aligned.m64n8k16.f32.bf16.bf16 {%0, %1, %2, %3}, %4, %5, p, 1, 1, 1, 1;\n}\n"
    : "+f"(d[OFF + 0]), "+f"(d[OFF + 1]), "+f"(d[OFF + 2]), "+f"(d[OFF + 3]) : "l"(da), "l"(db), "r"(sd));
}
template<int OFF, int NT> __device__ __forceinline__ void wg_ss_n32_ta(float (&d)[NT], uint64_t da, uint64_t db, int sd) {
  asm volatile("{\n.reg .pred p;\nsetp.ne.b32 p, %18, 0;\n"
    "wgmma.mma_async.sync.aligned.m64n32k16.f32.bf16.bf16 {%0, %1, %2, %3, %4, %5, %6, %7, %8, %9, %10, %11, %12, %13, %14, %15}, %16, %17, p, 1, 1, 1, 0;\n}\n"
    : "+f"(d[OFF + 0]), "+f"(d[OFF + 1]), "+f"(d[OFF + 2]), "+f"(d[OFF + 3]), "+f"(d[OFF + 4]), "+f"(d[OFF + 5]), "+f"(d[OFF + 6]), "+f"(d[OFF + 7]), "+f"(d[OFF + 8]), "+f"(d[OFF + 9]), "+f"(d[OFF + 10]), "+f"(d[OFF + 11]), "+f"(d[OFF + 12]), "+f"(d[OFF + 13]), "+f"(d[OFF + 14]), "+f"(d[OFF + 15]) : "l"(da), "l"(db), "r"(sd));
}

__device__ float g_gate[SEQ];
__device__ bf16 g_ox[SEQ * HD];

__device__ uint4 g_kvT[DM * 256];
__device__ unsigned g_ka_done, g_conv_done, g_k2_seen;
#define KC_BG 512
__device__ bf16 g_y2T[DM * SEQ];

constexpr int KC_UL = 73 * 16;
constexpr int KC_U = 4 * KC_UL;
constexpr int KC_K = 2080 * 4;
constexpr int KC_BUF = KC_U + KC_K;
constexpr int KC_EX = 4096, KC_BAR = KC_EX + 8192, KC_IN = KC_BAR + 64;
constexpr int KC_WG = 38912;
constexpr int KC_SMEM = 4 * KC_WG;
static_assert(KC_IN + 2 * KC_BUF <= KC_WG && KC_WG % 1024 == 0 && KC_IN + KC_BUF <= 32768, "kc smem");

__device__ __forceinline__ uint32_t bmul2(uint32_t a, uint32_t b) { uint32_t r; asm("mul.rn.bf16x2 %0, %1, %2;" : "=r"(r) : "r"(a), "r"(b)); return r; }
__device__ __forceinline__ uint32_t badd2(uint32_t a, uint32_t b) { uint32_t r; asm("add.rn.bf16x2 %0, %1, %2;" : "=r"(r) : "r"(a), "r"(b)); return r; }
__device__ __forceinline__ void cp_async16(uint32_t dst, const void* src) { asm volatile("cp.async.cg.shared.global [%0], [%1], 16;" ::"r"(dst), "l"(src) : "memory"); }

template <int G, int NA> __device__ __forceinline__ void kc_group(float (&acc)[NA], uint32_t ka, uint64_t db) {
  constexpr int D0 = 16 * (G >> 1) + 4 * (G & 1);
  uint32_t w[17];
#pragma unroll
  for (int i = 0; i < 17; i++) w[i] = lds_u32(ka + (16 * D0 - 12 + 4 * i) * 4);
  wg_fence();
#pragma unroll
  for (int d = 0; d < 4; d++) {
    const uint64_t d0 = db + (D0 + d), d1 = d0 + ((2 * KC_UL) >> 4);
    const uint32_t* x = w + 4 * d;
    if constexpr (NA == 32) { wg_rs_n64<0>(acc, x[3], x[4], x[2], x[3], d0, 1); wg_rs_n64<0>(acc, x[1], x[2], x[0], x[1], d1, 1); }
    if constexpr (NA == 24) { wg_rs_n48<0>(acc, x[3], x[4], x[2], x[3], d0, 1); wg_rs_n48<0>(acc, x[1], x[2], x[0], x[1], d1, 1); }
    if constexpr (NA == 16) { wg_rs_n32<0>(acc, x[3], x[4], x[2], x[3], d0, 1); wg_rs_n32<0>(acc, x[1], x[2], x[0], x[1], d1, 1); }
    if constexpr (NA == 8) { wg_rs_n16<0>(acc, x[3], x[4], x[2], x[3], d0, (G & 1) | d); wg_rs_n16<0>(acc, x[1], x[2], x[0], x[1], d1, 1); }
  }
  wg_commit();
  wg_wait<0>();
  fence_regs(acc);
}
template <int N> __device__ __forceinline__ void kc_widen(float (&o)[N + 8], const float (&a)[N], float zero) {
#pragma unroll
  for (int i = 0; i < N; i++) o[i] = a[i] + zero;
#pragma unroll
  for (int i = 0; i < 8; i++) asm volatile("add.f32 %0, %1, %1;" : "=f"(o[N + i]) : "f"(zero));
}
__device__ __forceinline__ void kc_mma(float (&a32)[32], uint32_t ka, uint64_t db, float zero) {
  float a8[8], a16[16], a24[24];
  kc_group<6>(a8, ka, db); kc_group<7>(a8, ka, db);
  kc_widen(a16, a8, zero);
  kc_group<4>(a16, ka, db); kc_group<5>(a16, ka, db);
  kc_widen(a24, a16, zero);
  kc_group<2>(a24, ka, db); kc_group<3>(a24, ka, db);
  kc_widen(a32, a24, zero);
  kc_group<0>(a32, ka, db); kc_group<1>(a32, ka, db);
}
template <int HI> __device__ __forceinline__ void kc_finish(float (&acc)[32], uint32_t ex, uint32_t ua, uint32_t oa, uint32_t D2, int barid) {
  constexpr int S0 = HI ? 4 : 16;
#pragma unroll
  for (int i = 0; i < 4; i++)
    sts_v4(ex + i * 512, make_uint4(__float_as_uint(acc[S0 + 4 * i]), __float_as_uint(acc[S0 + 4 * i + 1]), __float_as_uint(acc[S0 + 4 * i + 2]), __float_as_uint(acc[S0 + 4 * i + 3])));
  bar_sync(barid, 128);
#pragma unroll
  for (int p = 0; p < 2; p++) {
    uint32_t u[4], o[4];
    asm volatile("ldmatrix.sync.aligned.m8n8.x4.trans.shared.b16 {%0,%1,%2,%3}, [%4];" : "=r"(u[0]), "=r"(u[1]), "=r"(u[2]), "=r"(u[3]) : "r"(ua + p * 256) : "memory");
#pragma unroll
    for (int q = 0; q < 2; q++) {
      const int i = 2 * p + q, o0 = HI ? 20 + 4 * i : 4 * i;
      const uint4 x = lds_v4(ex + (HI ? -4096 : 4096) + i * 512);
      float y[4] = {__uint_as_float(x.x), __uint_as_float(x.y), __uint_as_float(x.z), __uint_as_float(x.w)};
      if (o0 < 32) {
#pragma unroll
        for (int e = 0; e < 4; e++) y[e] += acc[o0 < 32 ? o0 + e : 0];
      }
      o[2 * q] = badd2(pack_bf16(y[0], y[1]), bmul2(u[2 * q], D2));
      o[2 * q + 1] = badd2(pack_bf16(y[2], y[3]), bmul2(u[2 * q + 1], D2));
    }
    asm volatile("stmatrix.sync.aligned.m8n8.x4.trans.shared.b16 [%0], {%1,%2,%3,%4};" ::"r"(oa - p * 1024), "r"(o[0]), "r"(o[1]), "r"(o[2]), "r"(o[3]) : "memory");
  }
}

__device__ __forceinline__ void wait_count(const unsigned* p, unsigned n) {
#pragma unroll 1
  for (int it = 0; it < 4000000; it++) {
    unsigned v; asm volatile("ld.acquire.gpu.global.u32 %0, [%1];" : "=r"(v) : "l"(p) : "memory");
    if (v >= n) break;
    __nanosleep(200);
  }
  asm volatile("fence.proxy.async;" ::: "memory");
}
template <int NB> __device__ __forceinline__ void conv_wg(uint32_t wb, int barid, int ch, int step, int ch1, const CUtensorMap* tmY, const bf16* __restrict__ ssm_k,
                                                          const bf16* __restrict__ ssm_D) {
  const int t128 = threadIdx.x & 127, lane = t128 & 31, wq = t128 >> 5, g = lane >> 2, tq = lane & 3, mi = lane >> 3, r8 = lane & 7;
  const uint32_t bar = wb + KC_BAR;
  if (t128 == 0) { mbar_init(bar, 1); mbar_init(bar + 8, 1); asm volatile("fence.mbarrier_init.release.cluster;" ::: "memory"); }
  if (t128 < 32 * NB) sts_v4(wb + KC_IN + (t128 >> 5) * KC_BUF + ((t128 >> 3) & 3) * KC_UL + (64 + r8) * 16, make_uint4(0, 0, 0, 0));
  else if (t128 >= 64 && t128 < 64 + 8 * NB) sts_v4(wb + KC_IN + ((t128 >> 3) & 1) * KC_BUF + KC_U + ((t128 >> 2) & 1) * 4160 + (t128 & 3) * 16, make_uint4(0, 0, 0, 0));
  uint4 kw[2]; uint32_t pw[2];
  auto fetch_u = [&](int ch, int b) {
    if (t128 == 0) {
      mbar_expect_tx(bar + 8 * b, 4096);
#pragma unroll
      for (int c = 0; c < 4; c++)
        asm volatile("cp.async.bulk.shared::cluster.global.mbarrier::complete_tx::bytes [%0], [%1], 1024, [%2];"
                     ::"r"(wb + KC_IN + b * KC_BUF + c * KC_UL), "l"(g_kvT + ch * 256 + c * 64), "r"(bar + 8 * b) : "memory");
    }
  };
  auto fetch_k = [&](int ch) {
#pragma unroll
    for (int r = 0; r < 2; r++) {
      const int m = r * 128 + t128;
      const bf16* src = ssm_k + (size_t)ch * SEQ + m * 8;
      kw[r] = ldg_nc_v4(src);
      pw[r] = (m > 0) ? *reinterpret_cast<const uint32_t*>(src - 2) : 0u;
    }
  };
  auto stash = [&](int b) {
#pragma unroll
    for (int r = 0; r < 2; r++) {
      const uint32_t ka = wb + KC_IN + b * KC_BUF + KC_U + (16 + (r * 128 + t128) * 4) * 4;
      sts_v4(ka, make_uint4(prmt(kw[r].x, pw[r], 0x7610u), prmt(kw[r].y, kw[r].x, 0x7610u), prmt(kw[r].z, kw[r].y, 0x7610u), prmt(kw[r].w, kw[r].z, 0x7610u)));
      sts_v4(ka + 4160, make_uint4(prmt(kw[r].x, 0, 0x1032u), prmt(kw[r].y, 0, 0x1032u), prmt(kw[r].z, 0, 0x1032u), prmt(kw[r].w, 0, 0x1032u)));
    }
  };
  if (ch < ch1) { fetch_u(ch, 0); fetch_k(ch); stash(0); }
  fence_async_smem();
  bar_sync(barid, 128);
  const bool hi = __shfl_sync(0xffffffffu, wq >> 1, 0);
  int i = 0;
#pragma unroll 1
  for (; ch < ch1; i++) {
    const int b = (NB == 2) ? (i & 1) : 0, nb = (NB == 2) ? (b ^ 1) : 0, nxt = ch + step;
    const uint32_t ub = wb + KC_IN + b * KC_BUF;
    const uint32_t D2 = 0x10001u * (uint32_t)__bfloat16_as_ushort(ssm_D[ch]);
    if (nxt < ch1) { if (NB == 2) fetch_u(nxt, nb); fetch_k(nxt); }
    uint32_t dl = ((ub & 0x3FFFF) >> 4) | ((KC_UL >> 4) << 16);
    asm volatile("" : "+r"(dl));
    const uint64_t db = (8ull << 32) | __shfl_sync(0xffffffffu, dl + (lane >> 5), 0);
    const uint32_t ka = ub + KC_U + (g & 1) * 4160 + (((16 * (wq & 1) + g - 2 * tq) >> 1) + 16 + (wq >> 1) * 128) * 4;
    mbar_wait(bar + 8 * b, (NB == 2 ? i >> 1 : i) & 1);
    float acc[32];
    kc_mma(acc, ka, db, __uint_as_float(lds_u32(ub + KC_U)));
    if (t128 == 0) asm volatile("cp.async.bulk.wait_group.read 0;" ::: "memory");
    {
      const int n = 32 * (wq >> 1) + 8 * (mi >> 1) + r8, c = 2 * (wq & 1) + (mi & 1), a = 63 - n;
      const uint32_t ex = wb + KC_EX + wq * 2048 + lane * 16, ua = ub + c * KC_UL + n * 16, oa = wb + a * 64 + ((c ^ ((a >> 1) & 3)) << 4);
      if (hi) kc_finish<1>(acc, ex, ua, oa, D2, barid); else kc_finish<0>(acc, ex, ua, oa, D2, barid);
    }
    if (nxt < ch1) stash(nb);
    fence_async_smem();
    bar_sync(barid, 128);
    if (NB == 1 && nxt < ch1) fetch_u(nxt, 0);
    if (t128 == 0) {
      asm volatile("cp.async.bulk.tensor.2d.global.shared::cta.bulk_group [%0, {%2, %3}], [%1];" ::"l"(tmY), "r"(wb), "r"(0), "r"(ch * 64) : "memory");
      asm volatile("cp.async.bulk.commit_group;" ::: "memory");
    }
    ch = nxt;
  }
  if (t128 == 0) {
    asm volatile("cp.async.bulk.wait_group 0;\nfence.proxy.async.global;" ::: "memory");
    asm volatile("red.release.gpu.global.add.u32 [%0], %1;" ::"l"(&g_conv_done), "r"(i) : "memory");
  }
}

__global__ void __cluster_dims__(2, 1, 1) __launch_bounds__(512, 1)
kc_conv(const __grid_constant__ CUtensorMap tmY, const bf16* __restrict__ ssm_k, const bf16* __restrict__ ssm_D) {
  extern __shared__ __align__(1024) uint8_t smem[];
  const int wg = __shfl_sync(0xffffffffu, threadIdx.x >> 7, 0);
  conv_wg<2>(smem_u32(smem) + wg * KC_WG, 1 + wg, wg * 4 + blockIdx.x, 16, KC_BG, &tmY, ssm_k, ssm_D);
}

constexpr int KA_ST = 3, KA_SMEM = KA_ST * 65536 + 64;
__global__ void __cluster_dims__(2, 1, 1) __launch_bounds__(512, 1)
ka_prep(const __grid_constant__ CUtensorMap tmK, const __grid_constant__ CUtensorMap tmV, const bf16* __restrict__ q, const bf16* __restrict__ gate_w,
        const bf16* __restrict__ shift_k) {
  extern __shared__ __align__(1024) uint8_t smem[];
  const uint32_t sb = smem_u32(smem), bar = sb + KA_ST * 65536;
  const int tid = threadIdx.x, lane = tid & 31, warp = tid >> 5, g = lane >> 2, tq = lane & 3, mi = lane >> 3, r8 = lane & 7;
  auto issue = [&](int it) {
    const uint32_t dst = sb + (it % KA_ST) * 65536, b = bar + 8 * (it % KA_ST);
    mbar_expect_tx(b, 65536);
#pragma unroll
    for (int i = 0; i < 4; i++)
      asm volatile("cp.async.bulk.tensor.4d.shared::cluster.global.mbarrier::complete_tx::bytes [%0], [%1, {%3, %4, %5, %4}], [%2];"
                   ::"r"(dst + i * 16384), "l"((i & 2) ? &tmV : &tmK), "r"(b), "r"(blockIdx.x * 256 + (it >> 4) * 128 + (i & 1) * 64), "r"(0), "r"((it & 15) * 4) : "memory");
  };
  if (tid == 0) {
    for (int i = 0; i < KA_ST; i++) mbar_init(bar + 8 * i, 1);
    asm volatile("fence.mbarrier_init.release.cluster;" ::: "memory");
    for (int i = 0; i < KA_ST - 1; i++) issue(i);
  }
  uint4 gw[4], xv[4];
#pragma unroll
  for (int i = 0; i < 4; i++) gw[i] = *reinterpret_cast<const uint4*>(gate_w + i * 256 + lane * 8);
  const bf16* qrow = q + (size_t)(blockIdx.x * 512 + warp) * DM + lane * 8;
#pragma unroll
  for (int i = 0; i < 4; i++) xv[i] = ldg_nc_v4(qrow + i * 256);
  const uint32_t la = (warp >> 3) * 16384 + (8 * mi + r8) * 128 + (((warp & 7) ^ r8) << 4);
  uint32_t s0 = 0, s1 = 0, s2 = 0, s3 = 0, h0 = 0, h1 = 0;
  __syncthreads();
#pragma unroll 1
  for (int it = 0; it < 32; it++) {
    const int ch = blockIdx.x * 256 + (it >> 4) * 128 + warp * 8 + g;
    if ((it & 15) == 0) {
      const uint2 t = *reinterpret_cast<const uint2*>(shift_k + ch * 4);
      s0 = prmt(t.x, 0, 0x1010u); s1 = prmt(t.x, 0, 0x3232u); s2 = prmt(t.y, 0, 0x1010u); s3 = prmt(t.y, 0, 0x3232u);
      h0 = h1 = 0;
    }
    if (tid == 0 && it + KA_ST - 1 < 32) issue(it + KA_ST - 1);
    {
      float s = 0.f;
#pragma unroll
      for (int i = 0; i < 4; i++)
#pragma unroll
        for (int c = 0; c < 4; c++) {
          const uint32_t pr = bmul2(reinterpret_cast<const uint32_t*>(&xv[i])[c], reinterpret_cast<const uint32_t*>(&gw[i])[c]);
          s += bf_lo(pr) + bf_hi(pr);
        }
      if (it + 1 < 32) {
#pragma unroll
        for (int i = 0; i < 4; i++) xv[i] = ldg_nc_v4(qrow + (size_t)(it + 1) * 16 * DM + i * 256);
      }
#pragma unroll
      for (int o = 16; o > 0; o >>= 1) s += __shfl_xor_sync(0xffffffffu, s, o);
      if (lane == 0) { const float z = rbf(s); g_gate[blockIdx.x * 512 + it * 16 + warp] = rbf(1.f / (1.f + __expf(-z))); }
    }
    mbar_wait(bar + 8 * (it % KA_ST), (it / KA_ST) & 1);
    const uint32_t src = sb + (it % KA_ST) * 65536 + la;
    uint32_t kk[18], vv[16];
#pragma unroll
    for (int c = 0; c < 4; c++) {
      asm volatile("ldmatrix.sync.aligned.m8n8.x4.trans.shared.b16 {%0,%1,%2,%3}, [%4];" : "=r"(kk[2 + 4 * c]), "=r"(kk[3 + 4 * c]), "=r"(kk[4 + 4 * c]), "=r"(kk[5 + 4 * c]) : "r"(src + c * 4096) : "memory");
      asm volatile("ldmatrix.sync.aligned.m8n8.x4.trans.shared.b16 {%0,%1,%2,%3}, [%4];" : "=r"(vv[4 * c]), "=r"(vv[1 + 4 * c]), "=r"(vv[2 + 4 * c]), "=r"(vv[3 + 4 * c]) : "r"(src + 32768 + c * 4096) : "memory");
    }
    {
      const uint32_t a = __shfl_sync(0xffffffffu, kk[16], (lane & 28) | ((tq + 3) & 3)), b = __shfl_sync(0xffffffffu, kk[17], (lane & 28) | ((tq + 3) & 3));
      kk[0] = tq ? a : h0; kk[1] = tq ? b : h1;
      h0 = a; h1 = b;
    }
    uint4* dst = g_kvT + ch * 256 + 63 - (it & 15) * 4 - tq;
#pragma unroll
    for (int c = 0; c < 4; c++) {
      uint32_t o[4];
#pragma unroll
      for (int i = 0; i < 4; i++) {
        const int x = 2 + 4 * c + i;
        uint32_t a = bmul2(prmt(kk[x - 2], kk[x - 1], 0x5432u), s3);
        a = badd2(a, bmul2(kk[x - 1], s2));
        a = badd2(a, bmul2(prmt(kk[x - 1], kk[x], 0x5432u), s1));
        a = badd2(a, bmul2(kk[x], s0));
        o[i] = bmul2(a, vv[4 * c + i]);
      }
      dst[c * 64] = make_uint4(o[0], o[1], o[2], o[3]);
    }
    __syncthreads();
  }
  __threadfence();
  __syncthreads();
  if (tid == 0) asm volatile("red.release.gpu.global.add.u32 [%0], 1;" ::"l"(&g_ka_done) : "memory");
}

constexpr uint32_t XW_MEM = 0, XW_PROBE = 65536, XW_O = 131072, XW_VX = 262144, XW_VM = 524288, XW_SLOT = 1u << 20;
constexpr uint32_t XW_SX = 2u << 20, XW_SXS = 262144, XW_DRY = 4u << 20;
__device__ uint4 g_xw[(9 << 20) / 16];
__device__ __forceinline__ int nstep_() { int n; asm volatile("mov.u32 %0, %%nctaid.x;" : "=r"(n)); return n >> 1; }
#define NSTEP nstep_()
#define K1_DRY (gridDim.x < 128)
constexpr int KR = 24;
#define POLL_MAX ((int)(gridDim.x >> 7) * 200000)

constexpr uint32_t Q_WRES = 0, Q_XT = 65536, Q_STG = 98304;
constexpr uint32_t Q_MEMS = 131072, Q_KXEX = Q_MEMS + 8192, Q_QEX = Q_KXEX + 8192, Q_KEX = Q_QEX + 2048, Q_QF = Q_KEX + 2048, Q_KX = Q_QF + 2048,
                   Q_QX = Q_KX + 10240, Q_SMM = Q_QX + 8192, Q_SMX = Q_SMM + 2048, Q_VM = Q_SMX + 1536, Q_TAB = 196608;
static_assert(Q_VM + 1024 <= Q_TAB, "smem");
constexpr uint32_t V_WRES = 0, V_XT = 32768, V_STG = 98304, V_RED = 6144;
constexpr uint32_t V_MEMS = V_STG + 8192, V_VXEX = V_STG + 4 * 16384 + 7168, V_VXS = V_STG + 2 * 16384 + 8192, V_PS = V_STG + 5 * 16384 + 8192,
                   V_TAB = V_STG + 6 * 16384 + 8192, V_PF = V_STG + 16384 + 12288, V_OX = V_STG + 16384 + 8192;
constexpr int OR = 10;
constexpr uint32_t K1_BAR = 229376, K1_SMEM = K1_BAR + 256;
static_assert(K1_SMEM <= 232448, "smem");
constexpr uint32_t MB_X = 0, MB_S = 16, MB_A = 32, MB_B = 64, MB_C = 96, MB_D = 128, MB_P = 160;
enum { B_MEM = 1, B_GOK = 2, B_QF = 3, B_W0 = 4, B_W1 = 5, B_GOX = 6, B_GOQ = 7, B_VM = 8, B_KM = 9, B_SX = 10, B_S = 11, B_PD = 12, B_RED = 2, B_P = 3, B_GOV = 6, B_OX = 7, B_XF = 8 };

__device__ __forceinline__ uint4 ld_rlx(const void* p) {
  uint4 v; asm volatile("ld.relaxed.gpu.global.v4.u32 {%0,%1,%2,%3}, [%4];" : "=r"(v.x), "=r"(v.y), "=r"(v.z), "=r"(v.w) : "l"(p) : "memory"); return v;
}
__device__ __forceinline__ void st_rlx(void* p, uint32_t a, uint32_t b, uint32_t c, uint32_t d) {
  asm volatile("st.relaxed.gpu.global.v4.u32 [%0], {%1,%2,%3,%4};" ::"l"(p), "r"(a), "r"(b), "r"(c), "r"(d) : "memory");
}
__device__ __forceinline__ void st_rlx64(void* p, uint32_t a, uint32_t b) { asm volatile("st.relaxed.gpu.global.v2.u32 [%0], {%1,%2};" ::"l"(p), "r"(a), "r"(b) : "memory"); }
__device__ __forceinline__ void st_rlx32(void* p, uint32_t v) { asm volatile("st.relaxed.gpu.global.u32 [%0], %1;" ::"l"(p), "r"(v) : "memory"); }
__device__ __forceinline__ uint32_t tagw(uint32_t w, uint32_t ph) { return (w & ~1u) | ph; }
__device__ __forceinline__ uint32_t fu(float x) { return __float_as_uint(x); }
__device__ __forceinline__ float uf(uint32_t x) { return __uint_as_float(x); }
__device__ __forceinline__ void mma16816(float (&c)[4], uint32_t a0, uint32_t a1, uint32_t a2, uint32_t a3, uint32_t b0, uint32_t b1) {
  asm volatile("mma.sync.aligned.m16n8k16.row.col.f32.bf16.bf16.f32 {%0,%1,%2,%3}, {%4,%5,%6,%7}, {%8,%9}, {%0,%1,%2,%3};"
               : "+f"(c[0]), "+f"(c[1]), "+f"(c[2]), "+f"(c[3]) : "r"(a0), "r"(a1), "r"(a2), "r"(a3), "r"(b0), "r"(b1));
}
__device__ __forceinline__ void mma16816z(float (&c)[4], uint32_t a0, uint32_t a1, uint32_t a2, uint32_t a3, uint32_t b0, uint32_t b1) {
  asm volatile("mma.sync.aligned.m16n8k16.row.col.f32.bf16.bf16.f32 {%0,%1,%2,%3}, {%4,%5,%6,%7}, {%8,%9}, {%10,%10,%10,%10};"
               : "=f"(c[0]), "=f"(c[1]), "=f"(c[2]), "=f"(c[3]) : "r"(a0), "r"(a1), "r"(a2), "r"(a3), "r"(b0), "r"(b1), "f"(0.f));
}
__device__ __forceinline__ void mma1688(float (&c)[4], uint32_t a0, uint32_t a1, uint32_t b0) {
  asm volatile("mma.sync.aligned.m16n8k8.row.col.f32.bf16.bf16.f32 {%0,%1,%2,%3}, {%4,%5}, {%6}, {%0,%1,%2,%3};"
               : "+f"(c[0]), "+f"(c[1]), "+f"(c[2]), "+f"(c[3]) : "r"(a0), "r"(a1), "r"(b0));
}
__device__ __forceinline__ void ldsm4(uint32_t (&r)[4], uint32_t a) {
  asm volatile("ldmatrix.sync.aligned.m8n8.x4.shared.b16 {%0,%1,%2,%3}, [%4];" : "=r"(r[0]), "=r"(r[1]), "=r"(r[2]), "=r"(r[3]) : "r"(a) : "memory");
}
__device__ __forceinline__ void ldsm4t(uint32_t (&r)[4], uint32_t a) {
  asm volatile("ldmatrix.sync.aligned.m8n8.x4.trans.shared.b16 {%0,%1,%2,%3}, [%4];" : "=r"(r[0]), "=r"(r[1]), "=r"(r[2]), "=r"(r[3]) : "r"(a) : "memory");
}
__device__ __forceinline__ void stsm4t(uint32_t a, uint32_t r0, uint32_t r1, uint32_t r2, uint32_t r3) {
  asm volatile("stmatrix.sync.aligned.m8n8.x4.trans.shared.b16 [%0], {%1,%2,%3,%4};" ::"r"(a), "r"(r0), "r"(r1), "r"(r2), "r"(r3) : "memory");
}
__device__ __forceinline__ uint32_t movm(uint32_t x) { uint32_t y; asm volatile("movmatrix.sync.aligned.m8n8.trans.b16 %0, %1;" : "=r"(y) : "r"(x)); return y; }
__device__ __forceinline__ float2 lds_f2(uint32_t a) { float2 v; asm volatile("ld.shared.v2.f32 {%0,%1}, [%2];" : "=f"(v.x), "=f"(v.y) : "r"(a) : "memory"); return v; }
__device__ __forceinline__ float4 lds_f4(uint32_t a) { float4 v; asm volatile("ld.shared.v4.f32 {%0,%1,%2,%3}, [%4];" : "=f"(v.x), "=f"(v.y), "=f"(v.z), "=f"(v.w) : "r"(a) : "memory"); return v; }
__device__ __forceinline__ void sts_v2(uint32_t a, uint32_t x, uint32_t y) { asm volatile("st.shared.v2.u32 [%0], {%1,%2};" ::"r"(a), "r"(x), "r"(y) : "memory"); }
__device__ __forceinline__ void sts_f4(uint32_t a, float x, float y, float z, float w) { asm volatile("st.shared.v4.f32 [%0], {%1,%2,%3,%4};" ::"r"(a), "f"(x), "f"(y), "f"(z), "f"(w) : "memory"); }
__device__ __forceinline__ void sta_f4(uint32_t a, float x, float y, float z, float w, uint32_t bar) {
  asm volatile("st.async.weak.shared::cluster.mbarrier::complete_tx::bytes.v4.f32 [%0], {%1,%2,%3,%4}, [%5];" ::"r"(a), "f"(x), "f"(y), "f"(z), "f"(w), "r"(bar) : "memory");
}
__device__ __forceinline__ void sta_u4(uint32_t a, uint32_t x, uint32_t y, uint32_t z, uint32_t w, uint32_t bar) {
  asm volatile("st.async.weak.shared::cluster.mbarrier::complete_tx::bytes.v4.b32 [%0], {%1,%2,%3,%4}, [%5];" ::"r"(a), "r"(x), "r"(y), "r"(z), "r"(w), "r"(bar) : "memory");
}
template <int O, int N> __device__ __forceinline__ void send8(uint32_t a, const float (&d)[N], uint32_t bar) {
  sta_u4(a, pack_bf16(d[O], d[O + 1]), pack_bf16(d[O + 2], d[O + 3]), pack_bf16(d[O + 4], d[O + 5]), pack_bf16(d[O + 6], d[O + 7]), bar);
}
template <int O, int N> __device__ __forceinline__ uint4 pack8(const float (&d)[N]) {
  return make_uint4(pack_bf16(d[O], d[O + 1]), pack_bf16(d[O + 2], d[O + 3]), pack_bf16(d[O + 4], d[O + 5]), pack_bf16(d[O + 6], d[O + 7]));
}
template <int O, int N> __device__ __forceinline__ uint4 add8(const float (&d)[N], const uint4& p) {
  return make_uint4(pack_bf16(d[O] + bf_lo(p.x), d[O + 1] + bf_hi(p.x)), pack_bf16(d[O + 2] + bf_lo(p.y), d[O + 3] + bf_hi(p.y)),
                    pack_bf16(d[O + 4] + bf_lo(p.z), d[O + 5] + bf_hi(p.z)), pack_bf16(d[O + 6] + bf_lo(p.w), d[O + 7] + bf_hi(p.w)));
}
__device__ __forceinline__ void stsm4t(uint32_t a, const uint4& r) { stsm4t(a, r.x, r.y, r.z, r.w); }
__device__ __forceinline__ void sta_f2(uint32_t a, float x, float y, uint32_t bar) {
  asm volatile("st.async.weak.shared::cluster.mbarrier::complete_tx::bytes.v2.f32 [%0], {%1,%2}, [%3];" ::"r"(a), "f"(x), "f"(y), "r"(bar) : "memory");
}
__device__ __forceinline__ uint32_t mapa(uint32_t a, uint32_t r) { uint32_t o; asm volatile("mapa.shared::cluster.u32 %0, %1, %2;" : "=r"(o) : "r"(a), "r"(r)); return o; }
__device__ __forceinline__ void mbar_wait1(uint32_t bar, uint32_t parity) {
  asm volatile("{\n.reg .pred p;\n.reg .u32 c;\nmbarrier.try_wait.parity.shared::cta.b64 p, [%0], %1;\n@p bra.uni DONE;\nmov.u32 c, 0;\n"
               "AGAIN:\nmbarrier.try_wait.parity.shared::cta.b64 p, [%0], %1;\n@p bra.uni DONE;\nadd.u32 c, c, 1;\nsetp.lt.u32 p, c, 0x400000;\n@p bra.uni AGAIN;\nDONE:\n}"
               ::"r"(bar), "r"(parity) : "memory");
}
__device__ __forceinline__ void arrive_e(uint32_t bar) {
  asm volatile("{\n.reg .pred p;\nelect.sync _|p, 0xffffffff;\n@p mbarrier.arrive.shared::cta.b64 _, [%0];\n}" ::"r"(bar) : "memory");
}
__device__ __forceinline__ void expect_e(uint32_t bar, uint32_t bytes) {
  asm volatile("{\n.reg .pred p;\nelect.sync _|p, 0xffffffff;\n@p mbarrier.arrive.expect_tx.shared::cta.b64 _, [%0], %1;\n}" ::"r"(bar), "r"(bytes) : "memory");
}
__device__ __forceinline__ float ex2(float x) { float y; asm("ex2.approx.ftz.f32 %0, %1;" : "=f"(y) : "f"(x)); return y; }
__device__ __forceinline__ float rcp(float x) { float y; asm("rcp.approx.ftz.f32 %0, %1;" : "=f"(y) : "f"(x)); return y; }
__device__ __forceinline__ uint32_t phase_of(int n) { return (uint32_t)(((n >> 1) & 1) ^ 1); }
__device__ __forceinline__ uint32_t clk() { uint64_t c; asm volatile("mov.u64 %0, %%clock64;" : "=l"(c)::"memory"); return (uint32_t)c; }
__device__ __forceinline__ void wait_until(uint32_t t) {
  asm volatile("{\n.reg .pred p;\n.reg .u64 c;\n.reg .u32 l, h;\nAGAIN:\nmov.u64 c, %%clock64;\nmov.b64 {l, h}, c;\nsub.u32 l, l, %0;\nsetp.lt.s32 p, l, 0;\n@p bra.uni AGAIN;\n}" ::"r"(t) : "memory");
}
__device__ __forceinline__ void cluster_sync_all() { asm volatile("barrier.cluster.arrive.release.aligned;\nbarrier.cluster.wait.acquire.aligned;" ::: "memory"); }
__device__ __forceinline__ uint32_t side_off(uint32_t off, uint32_t c) { return off + (((c ^ __popc((off >> 12) & 0xb2u)) & 1u) << 12); }
#define SCHED() asm volatile("pmevent 1;" ::: "memory")
#define PIN64(x) asm volatile("" : "+l"(x))
#define PIN32(x) asm volatile("" : "+r"(x))

__device__ __forceinline__ uint32_t bad2(uint32_t a, uint32_t b, uint32_t ph) { uint32_t r; asm("lop3.b32 %0, %1, %2, %3, 0x7e;" : "=r"(r) : "r"(a), "r"(b), "r"(ph)); return r; }
__device__ __forceinline__ uint32_t or3(uint32_t a, uint32_t b, uint32_t c) { uint32_t r; asm("lop3.b32 %0, %1, %2, %3, 0xfe;" : "=r"(r) : "r"(a), "r"(b), "r"(c)); return r; }
template <int N> __device__ __forceinline__ bool tags_ok(const uint4 (&v)[N], uint32_t ph) {
  uint32_t bad;
  if constexpr (N == 2) bad = bad2(v[0].x, v[1].x, ph);
  if constexpr (N == 4) bad = or3(bad2(v[0].x, v[1].x, ph), bad2(v[2].x, v[3].x, ph), 0);
  if constexpr (N == 8) bad = or3(bad2(v[0].x, v[1].x, ph), bad2(v[2].x, v[3].x, ph), bad2(v[4].x, v[5].x, ph)), bad = or3(bad, bad2(v[6].x, v[7].x, ph), 0);
  return __all_sync(0xffffffffu, (bad & 1) == 0);
}
__device__ __forceinline__ void reload(uint4& v, const uint8_t* p, uint32_t ph) {
  asm volatile("{\n.reg .pred p;\n.reg .b32 t;\nxor.b32 t, %0, %5;\nand.b32 t, t, 1;\nsetp.ne.u32 p, t, 0;\n@p ld.relaxed.gpu.global.v4.u32 {%0,%1,%2,%3}, [%4];\n}"
               : "+r"(v.x), "+r"(v.y), "+r"(v.z), "+r"(v.w) : "l"(p), "r"(ph) : "memory");
}
__device__ __forceinline__ uint32_t lds_vol(uint32_t a) { uint32_t v; asm volatile("ld.volatile.shared.u32 %0, [%1];" : "=r"(v) : "r"(a) : "memory"); return v; }
#define DLY_UP 48
#define DLY_DN 16
__device__ __forceinline__ uint4 badd4(const uint4& a, const uint4& b) { return make_uint4(badd2(a.x, b.x), badd2(a.y, b.y), badd2(a.z, b.z), badd2(a.w, b.w)); }
template <int N, int ST> __device__ __forceinline__ void repoll(uint4 (&v)[N], const uint8_t* p0, const uint8_t* p1, uint32_t ph, int* dly = nullptr) {
  if (!tags_ok<N>(v, ph)) {
    if (dly) *dly = 1;
#pragma unroll 1
    for (int it = 0; it < POLL_MAX; it++) {
#pragma unroll
      for (int i = 0; i < N; i++) reload(v[i], (i < N / 2) ? p0 + i * ST : p1 + (i - N / 2) * ST, ph);
      if (tags_ok<N>(v, ph)) break;
    }
  }
#pragma unroll
  for (int i = 0; i < N; i++) asm volatile("" : "+r"(v[i].x), "+r"(v[i].y), "+r"(v[i].z), "+r"(v[i].w));
}
template <int N, int ST> __device__ __forceinline__ void poll(uint4 (&v)[N], const uint8_t* p0, const uint8_t* p1, uint32_t ph, int* dly = nullptr) {
#pragma unroll
  for (int i = 0; i < N; i++) v[i] = ld_rlx((i < N / 2) ? p0 + i * ST : p1 + (i - N / 2) * ST);
  repoll<N, ST>(v, p0, p1, ph, dly);
}
__device__ __forceinline__ uint4 tab(uint32_t tb, int k) {
  uint4 v; asm volatile("ld.volatile.shared.v4.u32 {%0,%1,%2,%3}, [%4];" : "=r"(v.x), "=r"(v.y), "=r"(v.z), "=r"(v.w) : "r"(tb + k * 4096) : "memory"); return v;
}
__device__ __forceinline__ uint32_t opaque(uint32_t slot, uint32_t v) { sts_u32(slot, v); return lds_vol(slot); }
__device__ __forceinline__ uint4 tabo(uint32_t a) { return tab(a, 0); }
__device__ __forceinline__ void quad_store(uint8_t* dst, const uint32_t (&ox)[4], int tq) {
  uint32_t a0 = ox[0], a1 = ox[1], a2 = ox[2], a3 = ox[3];
  const bool b0 = tq & 1, b1 = tq & 2;
  uint32_t s0 = b0 ? a0 : a1, s1 = b0 ? a2 : a3;
  s0 = __shfl_xor_sync(0xffffffffu, s0, 1); s1 = __shfl_xor_sync(0xffffffffu, s1, 1);
  if (b0) { a0 = s0; a2 = s1; } else { a1 = s0; a3 = s1; }
  uint32_t u0 = b1 ? a0 : a2, u1 = b1 ? a1 : a3;
  u0 = __shfl_xor_sync(0xffffffffu, u0, 2); u1 = __shfl_xor_sync(0xffffffffu, u1, 2);
  if (b1) { a0 = u0; a1 = u1; } else { a2 = u0; a3 = u1; }
  *reinterpret_cast<uint4*>(dst) = make_uint4(a0, a1, a2, a3);
}
__device__ __forceinline__ uint8_t* mkptr(uint32_t lo, uint32_t hi) { return reinterpret_cast<uint8_t*>(((uint64_t)hi << 32) | lo); }
__device__ __forceinline__ uint32_t plo(const void* p) { return (uint32_t)reinterpret_cast<uint64_t>(p); }
__device__ __forceinline__ uint32_t phi(const void* p) { return (uint32_t)(reinterpret_cast<uint64_t>(p) >> 32); }

#define TS(i) do { } while (0)
#define TSW(i, W) do { } while (0)
#define TSG(i) do { } while (0)
#define TSA(i) do { } while (0)
#define TS_DUMP() do { } while (0)
#define KORD 0
#define PROBE_N 3
#define XSKIP 0
#define XSKIP_LO 0
#define XSKIP_X 0
#define NOATT 0
#define XPOS 0
#define DLY_Q 2000
#define DLY_V 250
#define DLY_O 2100

#define GOI 0
template <int H> __device__ __forceinline__ void proj2_pre(uint32_t (&at)[8][4], uint32_t wres) {
#pragma unroll
  for (int m = 0; m < 4; m++) ldsm4t(at[4 * H + m], wres + (2 * H + (m >> 1)) * 2048 + (m & 1) * 16384);
}
__device__ constexpr int p2_s(int i) { return i == 0 ? 0 : i == 1 ? 1 : i == 9 ? 2 : i == 14 ? 3 : -1; }
__device__ constexpr int p2_r(int i) { return i - 2 - (i > 9) - (i > 14); }
__device__ constexpr int p2_pair(int i) { return p2_s(i) >= 0 ? 12 + p2_s(i) : p2_r(i); }
#define VMI 16
template <int GO> __device__ __forceinline__ void proj2(float (&d)[8], const uint32_t (&wf)[2][KR][4], uint32_t (&at)[8][4], uint32_t wres, uint32_t mems) {
  float acc[2][2][4];
  uint32_t b[2][4];
  ldsm4(b[0], mems + p2_pair(0) * 512);
#pragma unroll
  for (int i = 0; i < 16; i++) {
    if (i + 1 < 16) ldsm4(b[(i + 1) & 1], mems + p2_pair(i + 1) * 512);
    if (i >= 2 && i < 6) ldsm4t(at[i - 2], wres + (4 + ((i - 2) >> 1)) * 2048 + ((i - 2) & 1) * 16384);
    if (i >= 7 && i < 12 && i != 9) { const int m = i - 7 - (i > 9); ldsm4t(at[4 + m], wres + (6 + (m >> 1)) * 2048 + (m & 1) * 16384); }
    const uint32_t (&bb)[4] = b[i & 1];
    if (GOI > 0 && i == GOI && GO) bar_arrive(GO, 256);
#pragma unroll
    for (int u = 0; u < 2; u++)
#pragma unroll
      for (int t = 0; t < 2; t++) {
        const uint32_t* a = (p2_s(i) < 0) ? wf[t][p2_s(i) < 0 ? 2 * p2_r(i) + u : 0] : at[(p2_s(i) & 1) * 4 + 2 * u + t];
        if (i == 0) mma16816z(acc[t][u], a[0], a[1], a[2], a[3], bb[2 * u], bb[2 * u + 1]);
        else mma16816(acc[t][u], a[0], a[1], a[2], a[3], bb[2 * u], bb[2 * u + 1]);
      }
  }
#pragma unroll
  for (int t = 0; t < 2; t++)
#pragma unroll
    for (int e = 0; e < 4; e++) d[4 * t + e] = acc[t][0][e] + acc[t][1][e];
}
constexpr uint32_t SMEM0 = 0x400;
__device__ constexpr uint64_t cdesc(uint32_t off) { return (0x40000040ull << 32) | 0x10000u | ((SMEM0 + off) >> 4); }
template <uint32_t AOFF, uint32_t XOFF, int K0 = 0, int K1 = 32, bool IL = true> __device__ __forceinline__ void xproj(float (&ax)[16], const uint32_t (&wf)[KR][4]) {
#pragma unroll
  for (int i = K0; i < (XSKIP && AOFF >= XSKIP_LO && XOFF >= XSKIP_X ? (K0 == 0 ? 1 : K0) : K1); i++) {
    const int ks = !IL ? i : ((i & 3) == 3) ? KR + (i >> 2) : 3 * (i >> 2) + (i & 3);
    if (ks < KR) wg_rs_n32<0>(ax, wf[ks < KR ? ks : 0][0], wf[ks < KR ? ks : 0][1], wf[ks < KR ? ks : 0][2], wf[ks < KR ? ks : 0][3], cdesc(XOFF) + (ks >> 2) * 256 + (ks & 3) * 2, i != 0);
    else wg_ss_n32_ta<0>(ax, cdesc(AOFF) + (ks - KR) * 128, cdesc(XOFF) + (ks >> 2) * 256 + (ks & 3) * 2, 1);
  }
  wg_commit();
}
__device__ __forceinline__ void wg_ss_n40(float (&d)[20], uint64_t da, uint64_t db, int sd) {
  asm volatile("{\n.reg .pred p;\nsetp.ne.b32 p, %22, 0;\n"
    "wgmma.mma_async.sync.aligned.m64n40k16.f32.bf16.bf16 {%0, %1, %2, %3, %4, %5, %6, %7, %8, %9, %10, %11, %12, %13, %14, %15, %16, %17, %18, %19}, %20, %21, p, 1, 1, 0, 0;\n}\n"
    : "+f"(d[0]), "+f"(d[1]), "+f"(d[2]), "+f"(d[3]), "+f"(d[4]), "+f"(d[5]), "+f"(d[6]), "+f"(d[7]), "+f"(d[8]), "+f"(d[9]), "+f"(d[10]), "+f"(d[11]), "+f"(d[12]), "+f"(d[13]),
      "+f"(d[14]), "+f"(d[15]), "+f"(d[16]), "+f"(d[17]), "+f"(d[18]), "+f"(d[19]) : "l"(da), "l"(db), "r"(sd));
}
__device__ constexpr uint64_t cdesc0(uint32_t off, uint32_t lbo) { return (8ull << 32) | ((uint64_t)(lbo >> 4) << 16) | ((SMEM0 + off) >> 4); }
template <int P> __device__ __forceinline__ void q_shadow(const uint32_t (&wf)[2][KR][4], uint32_t dst, uint32_t (&at)[8][4], uint32_t wres) {
  float ax[2][16];
  wg_fence();
  xproj<Q_WRES, Q_XT + P * 32768>(ax[0], wf[0]);
  xproj<Q_WRES + 16384, Q_XT + P * 32768, 0, 10>(ax[1], wf[1]);
  wg_wait<1>(); fence_regs(ax[0]);
  stsm4t(dst, pack_bf16(ax[0][0], ax[0][1]), pack_bf16(ax[0][2], ax[0][3]), pack_bf16(ax[0][4], ax[0][5]), pack_bf16(ax[0][6], ax[0][7]));
  stsm4t(dst + 256, pack_bf16(ax[0][8], ax[0][9]), pack_bf16(ax[0][10], ax[0][11]), pack_bf16(ax[0][12], ax[0][13]), pack_bf16(ax[0][14], ax[0][15]));
  proj2_pre<0>(at, wres); proj2_pre<1>(at, wres);
  xproj<Q_WRES + 16384, Q_XT + P * 32768, 10, 32>(ax[1], wf[1]);
  asm volatile("cp.async.wait_all;" ::: "memory");
  wg_wait<0>(); fence_regs(ax[1]);
  stsm4t(dst + 4096, pack_bf16(ax[1][0], ax[1][1]), pack_bf16(ax[1][2], ax[1][3]), pack_bf16(ax[1][4], ax[1][5]), pack_bf16(ax[1][6], ax[1][7]));
  stsm4t(dst + 4096 + 256, pack_bf16(ax[1][8], ax[1][9]), pack_bf16(ax[1][10], ax[1][11]), pack_bf16(ax[1][12], ax[1][13]), pack_bf16(ax[1][14], ax[1][15]));
}
#define NW 0
#define NW1 0
template <int P, class F1, class F> __device__ __forceinline__ void k_shadow(const uint32_t (&wf)[2][KR][4], const uint4& t5, const uint32_t& bar, uint32_t tb, uint4& t0,
                                                                             uint4 (&kx)[2], uint32_t& tgo, F1&& mid1, F&& mid) {
  float ax[2][16];
  wg_fence();
  if (NW1 > 0) xproj<Q_WRES + 32768, Q_XT + P * 32768, 0, NW1, false>(ax[0], wf[0]);
  mid1();
  wg_fence();
  if (NW > 0) xproj<Q_WRES + 32768, Q_XT + P * 32768, NW1, NW1 + NW, false>(ax[0], wf[0]);
  mid();
  wg_fence();
  xproj<Q_WRES + 32768, Q_XT + P * 32768, NW1 + NW, 32, NW1 + NW == 0>(ax[0], wf[0]);
  xproj<Q_WRES + 49152, Q_XT + P * 32768, 0, 10>(ax[1], wf[1]);
  wg_wait<1>(); fence_regs(ax[0]);
  const uint4 k0 = pack8<0>(ax[0]), k1 = pack8<8>(ax[0]);
  sta_u4(t5.x, k0.x, k0.y, k0.z, k0.w, t5.y); sta_u4(t5.x + 512, k1.x, k1.y, k1.z, k1.w, t5.y);
  xproj<Q_WRES + 49152, Q_XT + P * 32768, 10, 25>(ax[1], wf[1]);
  xproj<Q_WRES + 49152, Q_XT + P * 32768, 25, 32>(ax[1], wf[1]);
  t0 = tab(tb, 0);
  tgo = lds_vol(tb + 16384 + 4);
  bar_sync(B_SX, 256);
  wg_wait<1>();
  bar_arrive(B_GOQ, 256);
  mbar_wait1(bar, P);
  const uint4 a0 = lds_v4(t5.z), b0 = lds_v4(t5.z + 512);
  wg_wait<0>(); fence_regs(ax[1]);
  const uint4 k2 = pack8<0>(ax[1]), k3 = pack8<8>(ax[1]);
  sta_u4(t5.x + 1024, k2.x, k2.y, k2.z, k2.w, t5.y + 32); sta_u4(t5.x + 1536, k3.x, k3.y, k3.z, k3.w, t5.y + 32);
  stsm4t(t5.w, badd4(k0, a0)); stsm4t(t5.w + 256, badd4(k1, b0));
  mbar_wait1(bar + 32, P);
  kx[0] = badd4(k2, lds_v4(t5.z + 1024)); kx[1] = badd4(k3, lds_v4(t5.z + 1536));
}
template <int P, class F> __device__ __forceinline__ void v1_shadow(const uint32_t (&vf)[KR][4], const uint32_t& rex, const uint32_t& rb, F&& mid) {
  float ax[16];
  wg_fence();
  xproj<V_WRES + 16384, V_XT + P * 32768, 0, 25>(ax, vf);
  xproj<V_WRES + 16384, V_XT + P * 32768, 25, 32>(ax, vf);
  mid();
  wg_wait<1>();
  bar_arrive(B_GOV, 256);
  wg_wait<0>(); fence_regs(ax);
  send8<0>(rex, ax, rb); send8<8>(rex + 512, ax, rb);
}
template <int P> __device__ __forceinline__ void v0_shadow(const uint32_t (&vf)[KR][4], uint32_t ex, uint32_t bar, uint8_t* xp, uint32_t vs, uint32_t pn) {
  float ax[16];
  wg_fence();
  xproj<V_WRES, V_XT + P * 32768>(ax, vf);
  mbar_wait1(bar, P);
  const uint4 a = lds_v4(ex), b = lds_v4(ex + 512);
  wg_wait<0>(); fence_regs(ax);
  const uint4 c = add8<0>(ax, a), d = add8<8>(ax, b);
  st_rlx(xp, tagw(c.x, pn), c.z, d.x, d.z); st_rlx(xp + 512, tagw(c.y, pn), c.w, d.y, d.w);
  sts_v4(vs, make_uint4(c.x, c.z, d.x, d.z)); sts_v4(vs + 512, make_uint4(c.y, c.w, d.y, d.w));
}
__device__ __forceinline__ void load_x(uint32_t sb, uint32_t xt, const CUtensorMap* tmX, int n, int j) {
  const uint32_t bar = sb + K1_BAR + MB_X + 8 * (n & 1);
  asm volatile("{\n.reg .pred p;\nelect.sync _|p, 0xffffffff;\n@p mbarrier.arrive.expect_tx.shared::cta.b64 _, [%2], 32768;\n"
               "@p cp.async.bulk.tensor.3d.shared::cluster.global.mbarrier::complete_tx::bytes [%0], [%1, {%3, %4, %5}], [%2];\n}"
               ::"r"(sb + xt + (n & 1) * 32768), "l"(tmX), "r"(bar), "r"(0), "r"(n * SEG), "r"(j * 8) : "memory");
}
__device__ __forceinline__ uint32_t probe_rtt(uint8_t* xw, uint32_t slot, uint32_t c) {
  uint8_t* p = xw + side_off(XW_PROBE, c) + blockIdx.x * 32;
  st_rlx(p, 0, 0, 0, 0); st_rlx(p + 16, 0, 0, 0, 0);
  uint32_t best = 1u << 30;
#pragma unroll 1
  for (int r = 0; r < PROBE_N; r++) {
    const uint32_t t0 = clk();
    uint32_t v; asm volatile("atom.relaxed.gpu.global.add.u32 %0, [%1], 1;" : "=r"(v) : "l"(p) : "memory");
    asm volatile("st.volatile.shared.u32 [%0], %1;" ::"r"(slot), "r"(v) : "memory");
    best = min(best, clk() - t0);
  }
  return best;
}
__device__ __forceinline__ uint32_t my_side(uint32_t bar) { return lds_u32(bar + 244) < lds_u32(bar + 240); }

constexpr float SM_SAFE = 24.f;
constexpr float SL2E = 0.08838834764831845f * 1.4426950408889634f;

template <int WG> __device__ __forceinline__ void qk_load_weights(uint32_t (&wf)[2][KR][4], uint32_t sb, const CUtensorMap* tm) {
  const int tid = threadIdx.x, lane = tid & 31, w = (tid >> 5) & 3, mi = lane >> 3, kr = (mi >> 1) * 8 + (lane & 7), h = blockIdx.x >> 2, j = blockIdx.x & 1;
  const uint32_t lo = kr * 128 + (((2 * w + (mi & 1)) ^ (kr & 7)) << 4), pb = sb + K1_BAR + MB_P + WG * 32, stg = sb + Q_STG + WG * 65536;
#pragma unroll
  for (int i = 0; i < 2 * KR; i++) asm volatile("" : "=r"(wf[i & 1][i >> 1][0]), "=r"(wf[i & 1][i >> 1][1]), "=r"(wf[i & 1][i >> 1][2]), "=r"(wf[i & 1][i >> 1][3]));
  if (!K1_DRY) {
#pragma unroll
  for (int c = 0; c < 3; c++) {
    mbar_wait1(pb + 8 * c, 0);
#pragma unroll
    for (int t = 0; t < 2; t++)
#pragma unroll
      for (int ks = 0; ks < 8; ks++) ldsm4t(wf[t][8 * c + ks], stg + (2 * (c & 1) + t) * 16384 + ks * 2048 + lo);
    if (c == 0) {
      bar_sync(B_W0 + WG, 128);
      if ((tid & 127) == 0) {
        mbar_expect_tx(pb + 16, 32768);
        for (int t = 0; t < 2; t++) tma_load_2d(stg + t * 16384, tm, h * DH + 64 * t, j * 512 + 256, pb + 16);
      }
      __syncwarp();
    }
  }
  mbar_wait1(pb + 24, 0);
  }
  TSG(2);
  cluster_sync_all();
}

__device__ __forceinline__ void role_q(uint32_t sb, const CUtensorMap* tmX, const CUtensorMap* tmW, uint8_t* __restrict__ xw) {
  uint32_t wf[2][KR][4];
  qk_load_weights<0>(wf, sb, tmW);
  const uint32_t tb0 = sb + Q_TAB + threadIdx.x * 16;
  {
    const uint32_t tb = tb0;
    const int h = blockIdx.x >> 2, j = blockIdx.x & 1, lane = threadIdx.x & 31, w = threadIdx.x >> 5, mi = lane >> 3, r8 = lane & 7, kr = (mi >> 1) * 8 + r8;
    const uint32_t BAR = sb + K1_BAR, l16 = sb + lane * 16, qex = l16 + Q_QEX + w * 512, bq = BAR + MB_A + 8 * w;
    const uint8_t* vxp = xw + XW_VX + (2 * h + j) * 4096 + w * 1024 + lane * 16;
    const uint8_t* op = xw + XW_O + (h >> 1) * 8192 + (4 * (h & 1) + 2 * j + (w >> 1)) * 512 + (lane >> 2) * 64 + (w & 1) * 32 + (lane & 3) * 8;
    sts_v4(tb, make_uint4(sb + Q_WRES + kr * 128 + (((2 * w + (mi & 1)) ^ (kr & 7)) << 4), l16, mapa(qex, j ^ 1), mapa(bq, j ^ 1)));
    sts_v4(tb + 4096, make_uint4(plo(vxp), phi(vxp), sb + Q_KX + mi * 640 + (8 * w + r8) * 16, bq));
    sts_v4(tb + 8192, make_uint4(qex, sb + Q_QF + (8 * (mi >> 1) + 2 * w + (mi & 1)) * 128 + r8 * 16, sb + Q_QF + (2 * (mi & 1) + (mi >> 1)) * 128 + r8 * 16, l16 + Q_SMX + (w & 1) * 8 + (w >> 1) * 4));
    sts_v4(tb + 12288, make_uint4(plo(op), 0, l16 + Q_SMM, sb + Q_VM + w * 256 + lane * 8));
    sts_v4(tb + 16384, make_uint4(BAR, (lane & 1) ? 0u : 1u, l16 + Q_SMX, sb + Q_QX + (2 * w + (mi & 1)) * 512 + (8 * (mi >> 1) + r8) * 16));
  }
  const uint32_t tb = opaque(tb0 + 20480, tb0);
  TSG(6);
  const int wu = __shfl_sync(0xffffffffu, threadIdx.x >> 5, 0);
  bar_arrive(B_SX, 256);
#pragma unroll 1
  for (int s = 0; s < NSTEP; s++) {
    {
      float q[8];
      {
        const uint4 t4 = tab(tb, 4), t0 = tab(tb, 0), tv = tab(tb, 1);
        expect_e(t4.x + MB_A + 8 * wu, 512);
        if (wu == 0) {
          if (XPOS == 0 ? s + 1 < NSTEP : s == 0) load_x(t4.x - K1_BAR, Q_XT, tmX, s + 1, blockIdx.x & 1);
        }
        {
          const uint8_t* vxp = mkptr(tv.x ^ ((s & 1) << 20), tv.y);
          cp_async16(tb + 20480, vxp); cp_async16(tb + 24576, vxp + 512);
        }
        mbar_wait1(t4.x + MB_X + 8 * (s & 1), (s >> 1) & 1);
        bar_sync(B_GOQ, 256);
        TS(6);
        uint32_t at[8][4];
        if (s & 1) q_shadow<1>(wf, t4.w, at, t0.x); else q_shadow<0>(wf, t4.w, at, t0.x);
        TS(7);
        bar_sync(B_MEM, 256);
        proj2<B_GOK>(q, wf, at, t0.x, t0.y + Q_MEMS);
        send8<0>(t0.z, q, t0.w);
        if (NW1 > 0) bar_arrive(B_PD, 256);
      }
      SCHED();
      TS(1);
      const uint32_t ph = phase_of(s), par = s & 1;
      const uint4 t1 = tab(tb, 1), t2 = tab(tb, 2), t3 = tab(tb, 3), t4 = tab(tb, 4);
      uint32_t kx[4][4];
#pragma unroll
      for (int i = 0; i < 4; i++) ldsm4(kx[i], t1.z + i * 2560);
      uint8_t* op = mkptr(t3.x ^ (par << 20), t1.y);
      const uint32_t tbit = t4.y & ph, smx = t4.z + 512 + (wu >> 1) * 512 + (wu & 1) * 8;
      SCHED();
      mbar_wait1(t1.w, par);
      stsm4t(t2.y, add8<0>(q, lds_v4(t2.x)));
      bar_arrive(B_QF, 256);
      bar_sync(B_W1, 128);
      {
        float c[4][4];
        uint32_t a[4][4];
#pragma unroll
        for (int i = 0; i < 4; i++) ldsm4(a[i], t2.z + i * 512);
#pragma unroll
        for (int i = 0; i < 2; i++) {
          mma16816z(c[2 * i], a[i][0], a[i][1], a[i][2], a[i][3], kx[i][0], kx[i][1]);
          mma16816z(c[2 * i + 1], a[i][0], a[i][1], a[i][2], a[i][3], kx[i][2], kx[i][3]);
        }
#pragma unroll
        for (int i = 2; i < 4; i++) {
          mma16816(c[2 * i - 4], a[i][0], a[i][1], a[i][2], a[i][3], kx[i][0], kx[i][1]);
          mma16816(c[2 * i - 3], a[i][0], a[i][1], a[i][2], a[i][3], kx[i][2], kx[i][3]);
        }
        const float x0 = ((c[0][0] + c[1][2]) + (c[2][0] + c[3][2])) * SL2E, x1 = ((c[0][1] + c[1][3]) + (c[2][1] + c[3][3])) * SL2E;
        sts_u32(t2.w, pack_bf16(ex2(x0), ex2(x1)) | ((fmaxf(fabsf(x0), fabsf(x1)) <= SM_SAFE) ? 0u : 0x80000000u));
        sts_v2(smx, fu(x0), fu(x1));
      }
      TS(2);
      uint4 vx[2] = {tab(tb, 5), tab(tb, 6)};
      bar_sync(B_S, 256);
      {
        const uint4 p = lds_v4(t4.z);
        const float4 r0 = lds_f4(t3.z), r1 = lds_f4(t3.z + 512);
        const float2 vm = lds_f2(t3.w);
        uint32_t o0, o1;
        auto pv = [&](const uint4& p, uint32_t pm) {
          float acc[3][4], u0[4], u1[4];
          mma16816z(acc[2], p.x, p.y, p.z, p.w, 0x3F803F80u, 0x3F803F80u);
          mma16816z(acc[0], p.x, p.y, p.z, p.w, vx[0].x, vx[0].y);
          mma16816z(acc[1], p.x, p.y, p.z, p.w, vx[1].x, vx[1].y);
          mma16816z(u0, p.x, p.y, p.z, p.w, vx[0].z, vx[0].w);
          mma16816z(u1, p.x, p.y, p.z, p.w, vx[1].z, vx[1].w);
          mma1688(acc[2], pm, 0u, 0x3F803F80u);
          mma1688(acc[0], pm, 0u, fu(vm.x));
          mma1688(acc[1], pm, 0u, fu(vm.y));
          const float inv = rcp(acc[2][0] + acc[2][2]);
          o0 = (pack_bf16((acc[0][0] + u0[2]) * inv, (acc[0][1] + u0[3]) * inv) & ~t4.y) | tbit; o1 = pack_bf16((acc[1][0] + u1[2]) * inv, (acc[1][1] + u1[3]) * inv);
        };
        const float m0 = (r0.x + r0.z) + (r1.x + r1.z), m1 = (r0.y + r0.w) + (r1.y + r1.w);
        const bool fast = __all_sync(0xffffffffu, (int)or3(or3(p.x, p.y, p.z), or3(p.w, bad2(vx[0].x, vx[1].x, ph) << 31, 0), (fmaxf(fabsf(m0), fabsf(m1)) <= SM_SAFE) ? 0u : 0x80000000u) >= 0);
        pv(p, pack_bf16(ex2(m0), ex2(m1)));
        if (fast) { st_rlx64(op, o0, o1);
 st_rlx64(op + 4096, o0, o1); }
        else {
          const uint8_t* vxp = mkptr(lds_vol(tb + 4096) ^ (par << 20), lds_vol(tb + 4096 + 4));
          repoll<2, 512>(vx, vxp, vxp + 512, ph);
          const float4 sa = lds_f4(t4.z + 512), sb2 = lds_f4(t4.z + 1024);
          float mx = fmaxf(fmaxf(fmaxf(fmaxf(sa.x, sa.y), fmaxf(sa.z, sa.w)), fmaxf(fmaxf(sb2.x, sb2.y), fmaxf(sb2.z, sb2.w))), fmaxf(m0, m1));
          mx = fmaxf(mx, __shfl_xor_sync(0xffffffffu, mx, 1));
          mx = fmaxf(mx, __shfl_xor_sync(0xffffffffu, mx, 2));
          pv(make_uint4(pack_bf16(ex2(sa.x - mx), ex2(sa.y - mx)), pack_bf16(ex2(sb2.x - mx), ex2(sb2.y - mx)), pack_bf16(ex2(sa.z - mx), ex2(sa.w - mx)),
                        pack_bf16(ex2(sb2.z - mx), ex2(sb2.w - mx))), pack_bf16(ex2(m0 - mx), ex2(m1 - mx)));
          st_rlx64(op, o0, o1); st_rlx64(op + 4096, o0, o1);
        }
      }
      bar_arrive(B_GOX, 256);
      SCHED();
      TS(5);
      TSA(12 + (threadIdx.x >> 5));
      {
        float c[20];
        fence_async_smem();
        bar_sync(B_KM, 256);
        wg_fence();
#pragma unroll
        for (int ks = 0; ks < 8; ks++) wg_ss_n40(c, cdesc0(Q_QX + ks * 1024, 512), cdesc0(Q_KX + ks * 1280, 640), ks != 0);
        wg_commit();
        uint4* sxp = reinterpret_cast<uint4*>(xw + (XW_SX + par * XW_SXS + ((blockIdx.x >> 2) * 2 + (blockIdx.x & 1)) * 4096 + (threadIdx.x & 31) * 16));
        wg_wait<0>(); fence_regs(c);
        bar_arrive(B_SX, 256);
        if (wu < 2) {
          sxp += wu * 64;
          st_rlx(sxp, tagw(fu(c[0]), ph), fu(c[1]), fu(c[4]), fu(c[5]));
          st_rlx(sxp + 32, tagw(fu(c[2]), ph), fu(c[3]), fu(c[6]), fu(c[7]));
          st_rlx(sxp + 192 - wu * 32, tagw(fu(c[16]), ph), fu(c[17]), fu(c[18]), fu(c[19]));
          if (wu == 1) {
            st_rlx(sxp + 64, tagw(fu(c[8]), ph), fu(c[9]), fu(c[12]), fu(c[13]));
            st_rlx(sxp + 96, tagw(fu(c[10]), ph), fu(c[11]), fu(c[14]), fu(c[15]));
          }
        }
      }
    }
  }
}

__device__ __forceinline__ void role_k(uint32_t sb, const CUtensorMap* tmW, uint8_t* __restrict__ xw, const bf16* __restrict__ mem0) {
  uint32_t wf[2][KR][4];
  qk_load_weights<1>(wf, sb, tmW);
  const uint32_t tb0 = sb + Q_TAB + threadIdx.x * 16;
  {
    const uint32_t tb = tb0;
    const int h = blockIdx.x >> 2, j = blockIdx.x & 1, lane = threadIdx.x & 31, w = (threadIdx.x >> 5) & 3, mi = lane >> 3, r8 = lane & 7, kr = (mi >> 1) * 8 + r8;
    const uint32_t BAR = sb + K1_BAR, l16 = sb + lane * 16, side = my_side(BAR);
    const uint8_t* p0 = xw + (w & 1) * 2048 + lane * 16 + side_off(XW_MEM + (j * 4 + (w >> 1)) * 8192, side);
    const uint8_t* vp = xw + side_off(XW_VM + (2 * h + j) * 8192, side) + w * 512 + lane * 16;
    const uint32_t smm = sb + Q_SMM + (w >> 1) * 512 + lane * 16 + (w & 1) * 8, kex = l16 + Q_KEX + w * 512, ex = l16 + Q_KXEX + w * 2048;
    sts_v4(tb, make_uint4(sb + Q_WRES + 32768 + kr * 128 + (((2 * w + (mi & 1)) ^ (kr & 7)) << 4), l16 + Q_MEMS + w * 2048, plo(p0), phi(p0)));
    sts_v4(tb + 4096, make_uint4(kex, BAR + MB_B + 8 * w, smm, sb + Q_QF + (8 * (mi & 1) + 2 * w + (mi >> 1)) * 128 + r8 * 16));
    sts_v4(tb + 8192, make_uint4(plo(vp), phi(vp), sb + Q_KX + (8 * (mi >> 1) + 2 * w + (mi & 1)) * 640 + (32 + r8) * 16, sb + Q_VM + w * 256 + lane * 8));
    sts_v4(tb + 12288, make_uint4(mapa(kex, j ^ 1), mapa(BAR + MB_B + 8 * w, j ^ 1), l16 + Q_MEMS, 0));
    sts_v4(tb + 20480, make_uint4(mapa(ex, j ^ 1), mapa(BAR + MB_C + 8 * w, j ^ 1), ex, sb + Q_KX + (2 * w + (mi & 1)) * 640 + (8 * (mi >> 1) + r8) * 16));
#pragma unroll
    for (int i = 0; i < 4; i++) sts_v4(l16 + Q_MEMS + w * 2048 + i * 512, ldg_nc_v4(mem0 + r8 * DM + j * 512 + (16 * w + 4 * i + mi) * 8));
  }
  const uint32_t tb = opaque(sb + Q_SMX + (threadIdx.x & 127) * 4, tb0);
  sts_u32(tb + 16384, DLY_Q);
  float k[8] = {};
  auto scores = [&](int s) {
    uint4 vm[2];
    const uint4 t1 = tab(tb, 1);
    const uint4 t4 = tab(tb, 2);
    const uint8_t* vp = mkptr(t4.x ^ ((s & 1) << 20), t4.y);
    const uint32_t vmd = t4.w;
    if (VMI == 16) { vm[0] = ld_rlx(vp); vm[1] = ld_rlx(vp + 2048); }
    mbar_wait1(t1.y, s & 1);
    const uint4 kp = lds_v4(t1.x);
    if (VMI == 17) { vm[0] = ld_rlx(vp); vm[1] = ld_rlx(vp + 2048); }
    const uint4 kf = add8<0>(k, kp);
    const uint32_t b0 = movm(kf.x), b1 = movm(kf.y), b2 = movm(kf.z), b3 = movm(kf.w);
    bar_sync(B_QF, 256);
    uint32_t a[4];
    ldsm4(a, t1.w);
    float c0[4], c1[4];
    mma16816z(c0, a[0], a[1], a[2], a[3], b0, b1);
    mma16816z(c1, a[0], a[1], a[2], a[3], b2, b3);
    sts_v2(t1.z, fu((c0[0] + c1[2]) * SL2E), fu((c0[1] + c1[3]) * SL2E));
    SCHED();
    repoll<2, 512>(vm, vp, vp + 2048, phase_of(s));
    sts_v2(vmd, pack_bf16(uf(vm[0].x) + uf(vm[1].x), uf(vm[0].y) + uf(vm[1].y)), pack_bf16(uf(vm[0].z) + uf(vm[1].z), uf(vm[0].w) + uf(vm[1].w)));
    TSW(12, 7);
    if (NW > 0) bar_sync(B_S, 256); else bar_arrive(B_S, 256);
    stsm4t(t4.z, kf);
    fence_async_smem();
    bar_arrive(B_KM, 256);
  };
  mbar_wait1(sb + K1_BAR + MB_X, 0);
#pragma unroll 1
  for (int s = 0; s < NSTEP; s++) {
    const uint32_t par = s & 1;
    uint32_t rk, rb;
    {
      auto mid1 = [&]() { if (s > 0) scores(s - 1); };
      uint4 t5, t0, kx[2];
      uint32_t bc, tgo;
      auto mid = [&]() {
        const int dq0 = max((int)lds_vol(tb + 16384) - DLY_DN, 0);
        t5 = tab(tb, 5); bc = t5.y ^ t5.x ^ t5.z;
        expect_e(bc, 1024); expect_e(bc + 32, 1024); expect_e(bc - 32, 512);
        if (NW1 + NW == 0) mbar_wait1(sb + K1_BAR + MB_X + 8 * par, (s >> 1) & 1);
        if (s > 0) bar_sync(B_GOX, 256);
        sts_v2(tb + 16384, dq0, clk() + dq0);
      };
      if (par) k_shadow<1>(wf, t5, bc, tb, t0, kx, tgo, mid1, mid); else k_shadow<0>(wf, t5, bc, tb, t0, kx, tgo, mid1, mid);
      const uint8_t* p0 = mkptr(t0.z ^ ((par ^ 1) << 20), t0.w);
      uint4 v[8];
      wait_until(tgo);
      int dq = 0;
#pragma unroll
      for (int i = 0; i < 8; i++) v[i] = ld_rlx(p0 + (i & 3) * 512 + (i >> 2) * 16384);
      stsm4t(t5.w + 5120, kx[0]); stsm4t(t5.w + 5120 + 256, kx[1]);
      uint32_t at[8][4];
      proj2_pre<0>(at, t0.x);
      TS(15);
      if (s > 0) {
        repoll<8, 512>(v, p0, p0 + 16384, phase_of(s - 1), &dq);
#pragma unroll
        for (int i = 0; i < 4; i++) sts_v4(t0.y + i * 512, badd4(v[i], v[i + 4]));
      }
      TSA(4 + (threadIdx.x >> 5));
      bar_arrive(B_MEM, 256);
      if (dq) asm volatile("red.shared.add.u32 [%0], %1;" ::"r"(tb + 16384), "r"(DLY_UP + DLY_DN) : "memory");
      const uint4 t3 = tab(tb, 3);
      proj2_pre<1>(at, t0.x);
      rk = t3.x; rb = t3.y;
      const uint32_t mems = t3.z;
      TS(9);
      if (GOI > 0) bar_sync(B_GOK, 256); else bar_sync(B_GOK, 128);
      proj2<0>(k, wf, at, t0.x, mems);
    }
    send8<0>(rk, k, rb);
    if (NW1 + NW > 0 && s + 1 < NSTEP) mbar_wait1(sb + K1_BAR + MB_X + 8 * (par ^ 1), ((s + 1) >> 1) & 1);
    if (NW1 > 0) bar_sync(B_PD, 256);
    TS(10);
  }
  scores(NSTEP - 1);
  bar_sync(B_GOX, 256);
  bar_sync(B_SX, 256);
}

template <int WG> __device__ __forceinline__ void role_v(uint32_t sb, const CUtensorMap* tmX, const bf16* __restrict__ Wo, const CUtensorMap* tmOx, uint8_t* __restrict__ xw, const bf16* __restrict__ mem0) {
  uint32_t vf[KR][4], of[2][OR][4];
  const uint32_t BAR = sb + K1_BAR;
  const int h = blockIdx.x >> 2, j = blockIdx.x & 1;
#pragma unroll
  for (int i = 0; i < KR; i++) asm volatile("" : "=r"(vf[i][0]), "=r"(vf[i][1]), "=r"(vf[i][2]), "=r"(vf[i][3]));
#pragma unroll
  for (int i = 0; i < 2 * OR; i++) asm volatile("" : "=r"(of[i & 1][i >> 1][0]), "=r"(of[i & 1][i >> 1][1]), "=r"(of[i & 1][i >> 1][2]), "=r"(of[i & 1][i >> 1][3]));
  if (!K1_DRY) {
    const int tid = threadIdx.x, lane = tid & 31, w = (tid >> 5) & 3, mi = lane >> 3, kr = (mi >> 1) * 8 + (lane & 7), g = lane >> 2, tq = lane & 3;
    const uint32_t lo = kr * 128 + (((2 * w + (mi & 1)) ^ (kr & 7)) << 4), pb = BAR + MB_P + WG * 32, stg = sb + V_STG + WG * 65536;
    const uint32_t wst = (w == 2) ? sb + V_XT + 32768 + WG * 16384 : stg + w * 16384;
    auto fetch_wo = [&]() {
      const bf16* gsrc = Wo + (size_t)(2048 * j + 1024 * WG + 256 * w + g) * DM + 32 * h + tq * 8;
#pragma unroll 8
      for (int i = 0; i < 32; i++) cp_async16(wst + (4 * i + (g >> 1)) * 128 + (((g ^ (g >> 2)) & 1) << 6) + tq * 16, gsrc + (size_t)(8 * i) * DM);
    };
    if (w >= 2) fetch_wo();
    mbar_wait1(pb, 0);
    TSG(2);
#pragma unroll
    for (int ks = 0; ks < KR; ks++) ldsm4t(vf[ks], stg + ks * 2048 + lo);
    bar_sync(B_W0 + WG, 128);
    if (w < 2) fetch_wo();
    asm volatile("cp.async.wait_all;" ::: "memory");
    __syncwarp();
    TSG(3);
    uint32_t tmp[2 * (16 - OR)][4];
    const uint32_t src = wst + (16 * (tq >> 1) + 4 * (tq & 1)) * 64 + g * 8, e = (tq & 1) << 6;
#pragma unroll
    for (int ks = 0; ks < 16; ks++) {
      const int pi = ks >> 1, si = (pi == 0) ? 0 : (pi == 3) ? 1 : (pi == 6) ? 2 : -1, ri = pi - 1 - (pi > 3) - (pi > 6);
      uint32_t (&f0)[4] = (si < 0) ? of[0][si < 0 ? 2 * ri + (ks & 1) : 0] : tmp[si < 0 ? 0 : 4 * si + 2 * (ks & 1)];
      uint32_t (&f1)[4] = (si < 0) ? of[1][si < 0 ? 2 * ri + (ks & 1) : 0] : tmp[si < 0 ? 0 : 4 * si + 2 * (ks & 1) + 1];
      const uint32_t a = src + (32 * pi + 2 * (ks & 1)) * 64;
      const float2 w0 = lds_f2(a + e), w1 = lds_f2(a + (e ^ 64)), w2 = lds_f2(a + 512 + e), w3 = lds_f2(a + 512 + (e ^ 64));
      f0[0] = prmt(fu(w0.x), fu(w1.x), 0x5410u); f0[1] = prmt(fu(w0.x), fu(w1.x), 0x7632u); f0[2] = prmt(fu(w2.x), fu(w3.x), 0x5410u); f0[3] = prmt(fu(w2.x), fu(w3.x), 0x7632u);
      f1[0] = prmt(fu(w0.y), fu(w1.y), 0x5410u); f1[1] = prmt(fu(w0.y), fu(w1.y), 0x7632u); f1[2] = prmt(fu(w2.y), fu(w3.y), 0x5410u); f1[3] = prmt(fu(w2.y), fu(w3.y), 0x7632u);
    }
    __syncwarp();
#pragma unroll
    for (int i = 0; i < 2 * (16 - OR); i++) sts_v4(stg + w * 16384 + i * 512 + lane * 16, make_uint4(tmp[i][0], tmp[i][1], tmp[i][2], tmp[i][3]));
    fence_async_smem();
  }
  TSG(4);
  cluster_sync_all();
  TSG(5);
  constexpr int T2 = WG ? 16384 - 2048 : -12288, T3 = T2 + 2048, T4 = -12288;
  uint32_t tb;
  {
    const int lane = threadIdx.x & 31, w = (threadIdx.x >> 5) & 3, warp = 4 * WG + w, mi = lane >> 3, r8 = lane & 7, kr = (mi >> 1) * 8 + r8, g = lane >> 2, tq = lane & 3;
    const uint32_t l16 = sb + lane * 16, side = my_side(BAR), t = sb + V_TAB + threadIdx.x * 16, ex = l16 + V_VXEX + w * 16384;
    sts_v4(t, make_uint4(w * 1024 + lane * 16 + side_off(XW_MEM + (j * 4 + WG) * 8192, side), XW_VM + (2 * h + (WG ^ j)) * 8192 + j * 2048 + w * 512 + lane * 16,
                         l16 + V_MEMS + warp * 1024, sb + V_WRES + WG * 16384 + kr * 128 + (((2 * w + (mi & 1)) ^ (kr & 7)) << 4)));
    sts_v4(t + 4096, make_uint4(side_off(XW_O + (8 * j + warp) * 8192, side) + lane * 16 + 2048,
                                XW_MEM + ((h >> 4) * 4 + j * 2 + ((h >> 3) & 1)) * 8192 + (h & 7) * 512 + w * 128 + r8 * 16 + (2 * (mi & 1) + (mi >> 1)) * 4,
                                l16 + V_STG + warp * 16384, sb + V_STG + V_RED + (mi >> 1) * 512 + w * 128 + (lane & 15) * 8));
    if (WG == 0) {
      sts_v4(t + T2, make_uint4(XW_VX + (2 * h + j) * 4096 + w * 1024 + lane * 16, l16 + V_VXS + w * 1024, ex, BAR + MB_A + 8 * w));
    } else {
      const int orow = 8 * (mi & 1) + r8;
      sts_v4(t + T2, make_uint4(mapa(ex, j ^ 1), mapa(BAR + MB_A + 8 * w, j ^ 1), l16 + V_VXS + w * 1024, l16 + V_PS));
      sts_v4(t + T3, make_uint4(XW_SX + 2 * h * 4096 + (w & 1) * 512 + lane * 16, l16 + V_PF + w * 16384, l16 + V_PS + (w >> 1) * 1536 + (w & 1) * 4, l16 + V_STG + w * 16384 + 7168));
      sts_v4(t + T4, make_uint4(XW_VM + (2 * h + j) * 8192 + w * 512 + lane * 16, sb + V_OX + orow * 128 + (((2 * w + (mi >> 1)) ^ r8) << 4), (w >> 1) * 1024, (6 + (w >> 1) - (w & 1)) * 512));
      const int lim = 8 * w + g - 2 * tq;
#pragma unroll
      for (int i = 0; i < 2; i++)
        sts_v4(l16 + V_STG + w * 16384 + 7168 + i * 512, make_uint4(16 * i > lim ? 0xff800000u : 0u, 16 * i + 1 > lim ? 0xff800000u : 0u, 16 * i + 8 > lim ? 0xff800000u : 0u, 16 * i + 9 > lim ? 0xff800000u : 0u));
    }
#pragma unroll
    for (int i = 0; i < 2; i++) sts_v4(l16 + V_MEMS + warp * 1024 + i * 512, ldg_nc_v4(mem0 + r8 * DM + j * 512 + (8 * warp + 4 * i + mi) * 8));
    tb = opaque(l16 + V_STG + warp * 16384 + V_RED, t);
  }
  TSG(6);
  auto warp0 = [&]() { return __any_sync(0xffffffffu, (tb & 0x600) == ((SMEM0 + V_TAB) & 0x600)); };
  uint32_t tpub = 0;
  int dd = DLY_V * 65536 + DLY_O;
#pragma unroll 1
  for (int s = -1; s <= NSTEP; s++) {
    const uint32_t ph = phase_of(s), slot = (s & 1) * XW_SLOT;
    const int n = s + 1, a = s - 1;
    const uint32_t pa = phase_of(a);
    uint32_t tm = 0;
    if (WG == 1 && s >= 1) {
      const uint4 t3 = tabo(tb + T3), t4 = tabo(tb + T4);
      const uint8_t* p0 = xw + (t3.x + (a & 1) * XW_SXS);
      const uint8_t* vp = xw + (t4.x + (slot ^ XW_SLOT));
#pragma unroll
      for (int p = 0; p < 2; p++) {
        cp_async16(t3.y + (4 * p) * 512, p0 + p * 4096 + t4.z); cp_async16(t3.y + (4 * p + 1) * 512, p0 + p * 4096 + 2 * t4.z);
        cp_async16(t3.y + (4 * p + 2) * 512, p0 + p * 4096 + t4.w); cp_async16(t3.y + (4 * p + 3) * 512, vp + p * 2048);
      }
    }
    if (s >= 0 && s < NSTEP) {
      const uint4 t0 = tab(tb, 0);
      uint32_t at[8][4];
#pragma unroll
      for (int i = 0; i < 8; i++) ldsm4t(at[i], t0.w + i * 2048);
      uint8_t* vp = xw + (t0.y + slot);
      const uint32_t mems = sb + V_MEMS + (t0.z & 511);
      int failed = 0;
      if (s > 0) {
        const uint8_t* p0 = xw + (t0.x + (slot ^ XW_SLOT));
        SCHED();
        wait_until(tpub);
        uint4 v[4];
        poll<4, 512>(v, p0, p0 + 16384, phase_of(s - 1), &failed);

#pragma unroll
        for (int i = 0; i < 2; i++) sts_v4(t0.z + i * 512, badd4(v[i], v[i + 2]));
      }
      bar_sync(B_MEM, 256);
      TSW(16, 0);
      {
        float acc[4][4];
        uint32_t b[3][4];
        ldsm4(b[0], mems + 12 * 512); ldsm4(b[1], mems + 13 * 512);
#pragma unroll
        for (int i = 0; i < 16; i++) {
          const int p = (i + 12) & 15;
          if (i + 2 < 16) ldsm4(b[(i + 2) % 3], mems + ((p + 2) & 15) * 512);
#pragma unroll
          for (int u = 0; u < 2; u++) {
            const int ks = 2 * p + u;
            const uint32_t (&a)[4] = (ks < KR) ? vf[ks < KR ? ks : 0] : at[ks < KR ? 0 : ks - KR];
            if (i < 2) mma16816z(acc[ks & 3], a[0], a[1], a[2], a[3], b[i % 3][2 * u], b[i % 3][2 * u + 1]);
            else mma16816(acc[ks & 3], a[0], a[1], a[2], a[3], b[i % 3][2 * u], b[i % 3][2 * u + 1]);
          }
        }
        const uint32_t c0 = tagw(fu((acc[0][0] + acc[1][0]) + (acc[2][0] + acc[3][0])), ph), c1 = fu((acc[0][1] + acc[1][1]) + (acc[2][1] + acc[3][1])),
                       c2 = fu((acc[0][2] + acc[1][2]) + (acc[2][2] + acc[3][2])), c3 = fu((acc[0][3] + acc[1][3]) + (acc[2][3] + acc[3][3]));
        st_rlx(vp, c0, c1, c2, c3); st_rlx(vp + 4096, c0, c1, c2, c3);
      }
      SCHED();
      dd += (failed ? DLY_UP : (dd >> 16) >= DLY_DN ? -DLY_DN : 0) * 65536;
      tm = clk() + (dd & 65535);
      TSW(17, 0);
    }
    if constexpr (WG == 0) {
      if (n < NSTEP) {
        const uint4 t2 = tabo(tb + T2);
        if (n + 1 < NSTEP && warp0()) load_x(sb, V_XT, tmX, n + 1, j);
        expect_e(t2.w, 1024);
        mbar_wait1(BAR + MB_X + 8 * (n & 1), (n >> 1) & 1);
        uint8_t* xp = xw + (t2.x + (slot ^ XW_SLOT));
        const uint32_t vs = t2.y + (n % 3) * 16384;
        bar_sync(B_GOV, 256);
        if (n & 1) v0_shadow<1>(vf, t2.z, t2.w, xp, vs, phase_of(n)); else v0_shadow<0>(vf, t2.z, t2.w, xp, vs, phase_of(n));
      }
    } else {
      uint4 t3, v[8];
      float4 ba, bb;
      uint32_t rex, rb;
      auto fetch = [&]() {
        { const uint4 t2 = tabo(tb + T2); rex = t2.x; rb = t2.y; }
        t3 = tabo(tb + T3);
        asm volatile("cp.async.wait_all;" ::: "memory");
#pragma unroll
        for (int i = 0; i < 8; i++) v[i] = lds_v4(t3.y + i * 512);
        ba = lds_f4(t3.w); bb = lds_f4(t3.w + 512);
      };
      if (n < NSTEP) {
        mbar_wait1(BAR + MB_X + 8 * (n & 1), (n >> 1) & 1);
        if (n & 1) v1_shadow<1>(vf, rex, rb, fetch); else v1_shadow<0>(vf, rex, rb, fetch);
      } else fetch();
      if (s >= 1 && !NOATT) {
        const uint4 t2 = tabo(tb + T2);
        if (!tags_ok<8>(v, pa)) {
          const uint8_t* p0 = xw + (lds_vol(tb + T3) + (a & 1) * XW_SXS);
          const uint4 t4 = tabo(tb + T4);
          const uint8_t* vp = xw + (t4.x + (slot ^ XW_SLOT));
#pragma unroll 1
          for (int it = 0; it < POLL_MAX; it++) {
#pragma unroll
            for (int p = 0; p < 2; p++) {
              v[4 * p] = ld_rlx(p0 + p * 4096 + t4.z); v[4 * p + 1] = ld_rlx(p0 + p * 4096 + 2 * t4.z);
              v[4 * p + 2] = ld_rlx(p0 + p * 4096 + t4.w); v[4 * p + 3] = ld_rlx(vp + p * 2048);
            }
            if (tags_ok<8>(v, pa)) break;
          }
        }
#pragma unroll
        for (int i = 0; i < 8; i++) asm volatile("" : "+r"(v[i].x), "+r"(v[i].y), "+r"(v[i].z), "+r"(v[i].w));
        const uint32_t vm0 = pack_bf16(uf(v[3].x) + uf(v[7].x), uf(v[3].y) + uf(v[7].y)), vm1 = pack_bf16(uf(v[3].z) + uf(v[7].z), uf(v[3].w) + uf(v[7].w));
        const bool hf = t3.z & 4;
        float e[10] = {fmaf(uf(v[0].x) + uf(v[4].x), SL2E, ba.x), fmaf(uf(v[0].y) + uf(v[4].y), SL2E, ba.y), fmaf(uf(v[0].z) + uf(v[4].z), SL2E, ba.z), fmaf(uf(v[0].w) + uf(v[4].w), SL2E, ba.w),
                       fmaf(uf(v[1].x) + uf(v[5].x), SL2E, bb.x), fmaf(uf(v[1].y) + uf(v[5].y), SL2E, bb.y), fmaf(uf(v[1].z) + uf(v[5].z), SL2E, bb.z), fmaf(uf(v[1].w) + uf(v[5].w), SL2E, bb.w),
                       (uf(hf ? v[2].z : v[2].x) + uf(hf ? v[6].z : v[6].x)) * SL2E, (uf(hf ? v[2].w : v[2].y) + uf(hf ? v[6].w : v[6].y)) * SL2E};
        float mx = fmaxf(fmaxf(fmaxf(fmaxf(e[0], e[1]), fmaxf(e[2], e[3])), fmaxf(fmaxf(e[4], e[5]), fmaxf(e[6], e[7]))), fmaxf(e[8], e[9]));
        mx = fmaxf(mx, __shfl_xor_sync(0xffffffffu, mx, 1));
        mx = fmaxf(mx, __shfl_xor_sync(0xffffffffu, mx, 2));
        const uint32_t vs = t2.z + (a % 3) * 16384, oxs = lds_vol(tb + T4 + 4);
        const uint4 v0 = lds_v4(vs), v1 = lds_v4(vs + 512);
#pragma unroll
        for (int i = 0; i < 10; i++) e[i] = ex2(e[i] - mx);
        float sum = ((e[0] + e[1]) + (e[2] + e[3])) + ((e[4] + e[5]) + (e[6] + e[7])) + (e[8] + e[9]);
        sum += __shfl_xor_sync(0xffffffffu, sum, 1);
        sum += __shfl_xor_sync(0xffffffffu, sum, 2);
        const float inv = rcp(sum);
#pragma unroll
        for (int i = 0; i < 5; i++) sts_u32(t3.z + (i >> 1) * 512 + (i & 1) * 8, pack_bf16(e[2 * i] * inv, e[2 * i + 1] * inv));
        asm volatile("cp.async.bulk.wait_group.read 0;" ::: "memory");
        bar_sync(B_P, 128);
        uint4 q[5];
#pragma unroll
        for (int i = 0; i < 5; i++) q[i] = lds_v4(t2.w + (i + (i > 0)) * 512);
        float c[4][4];
        mma16816z(c[2], q[2].x, q[2].y, q[2].z, q[2].w, v0.x, v0.y); mma16816z(c[3], q[2].x, q[2].y, q[2].z, q[2].w, v1.x, v1.y);
        mma16816z(c[0], q[0].x, q[0].y, q[0].z, q[0].w, v0.x, v0.y); mma16816z(c[1], q[0].x, q[0].y, q[0].z, q[0].w, v1.x, v1.y);
        mma16816(c[2], q[3].x, q[3].y, q[3].z, q[3].w, v0.z, v0.w); mma16816(c[3], q[3].x, q[3].y, q[3].z, q[3].w, v1.z, v1.w);
        mma1688(c[0], q[1].x, q[1].y, vm0); mma1688(c[1], q[1].x, q[1].y, vm1);
        mma1688(c[2], q[4].x, q[4].y, vm0); mma1688(c[3], q[4].x, q[4].y, vm1);
#pragma unroll
        for (int m = 0; m < 2; m++)
          asm volatile("stmatrix.sync.aligned.m8n8.x4.shared.b16 [%0], {%1,%2,%3,%4};" ::"r"(oxs + m * 2048), "r"(pack_bf16(c[2 * m][0], c[2 * m][1])), "r"(pack_bf16(c[2 * m][2], c[2 * m][3])),
                       "r"(pack_bf16(c[2 * m + 1][0], c[2 * m + 1][1])), "r"(pack_bf16(c[2 * m + 1][2], c[2 * m + 1][3])) : "memory");
      }
    }
    TSW(19, 0); TSW(20, 4);
    if (s < 0) TSG(7);
    if (s >= 0 && s < NSTEP) {
      const uint4 t1 = tab(tb, 1);
      const uint8_t* op = xw + (t1.x + slot) - 2048;
      const uint32_t wo = t1.z;
      uint4 at[4];
#pragma unroll
      for (int i = 0; i < 4; i++) at[i] = lds_v4(wo + i * 512);
      uint8_t* mp = xw + (t1.y + slot);
      const uint32_t tsel = (t1.y & 12) ? 0u : 1u;
      SCHED();
      wait_until(tm);
      TSW(22, 0);
      int nmiss = 0;
      uint4 o[8];
#pragma unroll
      for (int i = 0; i < 8; i++) o[i] = ld_rlx(op + i * 512);
      float acc[2][2][4];
#pragma unroll
      for (int gq = 0; gq < 4; gq++) {
        if (!__all_sync(0xffffffffu, (bad2(o[2 * gq].x, o[2 * gq + 1].x, ph) & 1) == 0)) {
          nmiss |= 1 << gq;
#pragma unroll 1
          for (int it = 0; it < POLL_MAX; it++) {
#pragma unroll
            for (int i = 2 * gq; i < 8; i++) reload(o[i], op + i * 512, ph);
            if (__all_sync(0xffffffffu, (bad2(o[2 * gq].x, o[2 * gq + 1].x, ph) & 1) == 0)) break;
          }
        }
        if (gq == 0) TSW(21, 0);
        if (gq == 3) TSA(8 + (threadIdx.x >> 5));
#pragma unroll
        for (int i = 2 * gq; i < 2 * gq + 2; i++) {
          const int si = (i == 0) ? 0 : (i == 3) ? 1 : (i == 6) ? 2 : -1, ri = i - 1 - (i > 3) - (i > 6);
#pragma unroll
          for (int u = 0; u < 2; u++)
#pragma unroll
            for (int mt = 0; mt < 2; mt++) {
              const uint32_t b0 = u ? o[i].z : o[i].x, b1 = u ? o[i].w : o[i].y;
              if (si < 0) mma16816(acc[mt][u], of[mt][si < 0 ? 2 * ri + u : 0][0], of[mt][si < 0 ? 2 * ri + u : 0][1], of[mt][si < 0 ? 2 * ri + u : 0][2], of[mt][si < 0 ? 2 * ri + u : 0][3], b0, b1);
              else {
                const uint4 a = at[2 * u + mt];
                if (i == 0) mma16816z(acc[mt][u], a.x, a.y, a.z, a.w, b0, b1); else mma16816(acc[mt][u], a.x, a.y, a.z, a.w, b0, b1);
                if (si < 2) at[2 * u + mt] = lds_v4(wo + (4 * (si + 1) + 2 * u + mt) * 512);
              }
            }
        }
      }
#pragma unroll
      for (int mt = 0; mt < 2; mt++)
        sts_f4(wo + V_RED + mt * 512, acc[mt][0][0] + acc[mt][1][0], acc[mt][0][2] + acc[mt][1][2], acc[mt][0][1] + acc[mt][1][1], acc[mt][0][3] + acc[mt][1][3]);
      if constexpr (WG == 1) bar_arrive(B_RED, 256);
      if constexpr (WG == 0) {
        bar_sync(B_RED, 256);
        float2 r[8];
#pragma unroll
        for (int i = 0; i < 8; i++) r[i] = lds_f2(t1.w + i * 16384);
        const uint32_t mw = (pack_bf16(((r[0].x + r[1].x) + (r[2].x + r[3].x)) + ((r[4].x + r[5].x) + (r[6].x + r[7].x)),
                                       ((r[0].y + r[1].y) + (r[2].y + r[3].y)) + ((r[4].y + r[5].y) + (r[6].y + r[7].y))) & ~tsel) | (tsel & ph);
        st_rlx32(mp, mw); st_rlx32(mp + 4096, mw);
      }
      SCHED();
      if (WG == 0) TSA(2 + (threadIdx.x >> 5));
      dd += nmiss ? DLY_UP : (dd & 65535) >= DLY_DN ? -DLY_DN : 0;
      tpub = clk() + (dd >> 16);
      TSW(23, 0);
    }
    if (WG == 1 && s >= 1) {
      fence_async_smem();
      if (warp0()) {
        bar_sync(B_OX, 128);
        if (!K1_DRY)
          asm volatile("{\n.reg .pred p;\nelect.sync _|p, 0xffffffff;\n@p cp.async.bulk.tensor.2d.global.shared::cta.bulk_group [%0, {%2, %3}], [%1];\ncp.async.bulk.commit_group;\n}"
                       ::"l"(tmOx), "r"(sb + V_OX), "r"(h * DH + 64 * j), "r"(a * SEG) : "memory");
      } else bar_arrive(B_OX, 128);
    }
  }
  if (WG == 1) asm volatile("cp.async.bulk.wait_group 0;" ::: "memory");
}

__global__ void __cluster_dims__(2, 1, 1) __launch_bounds__(256, 1)
k1_rec(const __grid_constant__ CUtensorMap tmX, const __grid_constant__ CUtensorMap tmWq, const __grid_constant__ CUtensorMap tmWk,
       const __grid_constant__ CUtensorMap tmWv, const __grid_constant__ CUtensorMap tmOx, uint8_t* __restrict__ xw, const bf16* __restrict__ mem0, const bf16* Wo) {
  extern __shared__ __align__(1024) uint8_t smem[];
  const uint32_t sb = smem_u32(smem);
  if ((sb & 0xFFFFFFu) != SMEM0) __trap();
  {
    const int tid = threadIdx.x, wg = tid >> 7, cta = blockIdx.x, h = cta >> 2, j = cta & 1;
    const uint32_t BAR = sb + K1_BAR;
    if (tid == 0) {
      mbar_init(BAR + MB_X, 1); mbar_init(BAR + MB_X + 8, 1); mbar_init(BAR + MB_S, 5);
      for (int i = 0; i < 24; i++) mbar_init(BAR + MB_A + 8 * i, 1);
      asm volatile("fence.mbarrier_init.release.cluster;" ::: "memory");
    }
    if (tid >= 64 && tid < 128) {
      bar_arrive(0, 256);
      if ((tid & 31) == 0) sts_u32(BAR + 240 + ((tid >> 3) & 4), probe_rtt(xw, BAR + 248 + ((tid >> 3) & 4), (tid >> 5) & 1));
      __syncwarp();
      bar_sync(15, 96);
    } else {
      bar_sync(0, 256);
      if (tid < 32) bar_arrive(15, 96);
    }
    TSG(16);
#define WPF 0
    if (WPF && tid >= 64 && tid < 68 && !K1_DRY)
      asm volatile("cp.async.bulk.prefetch.L2.global [%0], %1;" ::"l"(Wo + (size_t)cta * 32768 + (tid & 3) * 8192), "r"(16384) : "memory");
    if (tid == 96) asm volatile("prefetch.global.L2 [%0];" ::"l"(mem0 + cta * 64) : "memory");
    if ((tid & 127) == 0 && !K1_DRY) {
      const uint32_t pb = BAR + MB_P + wg * 32;
      if (!(cta & 2)) {
        const CUtensorMap* tm = wg ? &tmWk : &tmWq;
        for (int c = 0; c < 2; c++) {
          mbar_expect_tx(pb + 8 * c, 32768);
          for (int t = 0; t < 2; t++) tma_load_2d(sb + Q_STG + wg * 65536 + (2 * c + t) * 16384, tm, h * DH + 64 * t, j * 512 + 128 * c, pb + 8 * c);
        }
        mbar_expect_tx(pb + 24, 32768);
        for (int t = 0; t < 2; t++) tma_load_2d(sb + Q_WRES + wg * 32768 + t * 16384, tm, h * DH + 64 * t, j * 512 + 384, pb + 24);
      } else {
        mbar_expect_tx(pb, 65536);
        for (int c = 0; c < 3; c++) tma_load_2d(sb + V_STG + wg * 65536 + c * 16384, &tmWv, h * DH + 64 * (wg ^ j), j * 512 + 128 * c, pb);
        tma_load_2d(sb + V_WRES + wg * 16384, &tmWv, h * DH + 64 * (wg ^ j), j * 512 + 384, pb);
      }
    }
    __syncwarp();
    if (tid < 32) load_x(sb, (cta & 2) ? V_XT : Q_XT, &tmX, 0, j);
  }
  const int role = __shfl_sync(0xffffffffu, (threadIdx.x >> 7) | (blockIdx.x & 2), 0);
  if (role == 0) role_q(sb, &tmX, &tmWq, xw);
  else if (role == 1) role_k(sb, &tmWk, xw, mem0);
  else if (role == 2) role_v<0>(sb, &tmX, Wo, &tmOx, xw, mem0);
  else role_v<1>(sb, &tmX, Wo, &tmOx, xw, mem0);
  asm volatile("griddepcontrol.launch_dependents;" ::: "memory");
  TS_DUMP();
  TSG(29);
}

constexpr int G_STAGES = 5;
constexpr int G_STAGE_BYTES = 32768;
constexpr int G_SMEM = (G_STAGES + 2) * G_STAGE_BYTES + 1024 + 256;

template <int EPI>
__global__ void __launch_bounds__(544, 1)
k2_gemm(const __grid_constant__ CUtensorMap tmA, const __grid_constant__ CUtensorMap tmB, const __grid_constant__ CUtensorMap tmY,
        const __grid_constant__ CUtensorMap tmQ, const __grid_constant__ CUtensorMap tmOut, const __grid_constant__ CUtensorMap tmYo,
        const bf16* __restrict__ ssm_k, const bf16* __restrict__ ssm_D, int kblocks) {
  extern __shared__ uint8_t smem_raw[];
  const uint32_t sb = (smem_u32(smem_raw) + 1023) & ~1023u;
  const uint32_t ysm = sb + G_STAGES * G_STAGE_BYTES;
  const uint32_t qsm = ysm + G_STAGE_BYTES;
  const uint32_t bars = qsm + G_STAGE_BYTES;
  const int tid = threadIdx.x, warp = __shfl_sync(0xffffffffu, tid >> 5, 0), lane = tid & 31;
  const int n0 = blockIdx.x * 128, m0 = blockIdx.y * 128;
#define TS2(i)
#define TS3(i)
  TS2(30);
  if (tid == 0) {
    for (int s = 0; s < G_STAGES; s++) { mbar_init(bars + 8 * s, 1); mbar_init(bars + 64 + 8 * s, 2); }
    mbar_init(bars + 128, 2);
    asm volatile("fence.mbarrier_init.release.cluster;" ::: "memory");
  }
  __syncthreads();
  if (warp == 16) {
    if (lane == 0) {
      int st = 0; uint32_t ph = 1;
      asm volatile("griddepcontrol.wait;" ::: "memory");
      for (int kb = 0; kb < kblocks; kb++) {
        mbar_wait(bars + 64 + 8 * st, ph);
        const uint32_t dst = sb + st * G_STAGE_BYTES, fb = bars + 8 * st;
        mbar_expect_tx(fb, G_STAGE_BYTES);
        tma_load_2d(dst, &tmA, kb * 64, m0, fb);
        tma_load_2d(dst + 16384, &tmB, n0, kb * 64, fb);
        tma_load_2d(dst + 24576, &tmB, n0 + 64, kb * 64, fb);
        if (++st == G_STAGES) { st = 0; ph ^= 1; }
      }
    }
  } else if (warp >= 8) {
    const int cw = (warp >> 2) & 1;
    if ((tid & 127) == 0 && KC_BG + cw * 128 < DM) wait_count(&g_ka_done, 4);
    conv_wg<1>(ysm + cw * G_STAGE_BYTES, 2 + cw, KC_BG + cw * 128 + blockIdx.y * gridDim.x + blockIdx.x, 256, DM, &tmYo, ssm_k, ssm_D);
    TS3(26);
    if (tid == 256) {
      wait_count(&g_conv_done, DM);
      mbar_expect_tx(bars + 128, 32768);
      tma_load_2d(ysm, &tmY, m0, n0, bars + 128);
      tma_load_2d(ysm + 16384, &tmY, m0 + 64, n0, bars + 128);
      if (atomicAdd(&g_k2_seen, 1) == 127) { g_ka_done = 0; g_conv_done = 0; g_k2_seen = 0; }
    } else if (tid == 384) {
      mbar_expect_tx(bars + 128, 32768);
      tma_load_2d(qsm, &tmQ, n0, m0, bars + 128);
      tma_load_2d(qsm + 16384, &tmQ, n0 + 64, m0, bars + 128);
    }
  } else {
    const int wg = warp >> 2;
    float acc[64];
    int st = 0; uint32_t ph = 0;
    for (int kb = 0; kb < kblocks; kb++) {
      mbar_wait(bars + 8 * st, ph);
      const uint32_t a = sb + st * G_STAGE_BYTES + wg * 8192, b = sb + st * G_STAGE_BYTES + 16384;
      const uint64_t da = make_desc(a, 16, 1024, 1), db = make_desc(b, 8192, 1024, 1);
      wg_fence();
#pragma unroll
      for (int ks = 0; ks < 4; ks++) wg_ss_n128_tb<0>(acc, da + ks * 2, db + ks * 128, (kb | ks) != 0);
      wg_commit();
      wg_wait<1>();
      if (kb > 0) {
        const int ps = (st == 0) ? G_STAGES - 1 : st - 1;
        if ((tid & 127) == 0) mbar_arrive(bars + 64 + 8 * ps);
      }
      if (++st == G_STAGES) { st = 0; ph ^= 1; }
    }
    wg_wait<0>(); fence_regs(acc);
    TS2(27);
    const int g = lane >> 2;
    const int rl = wg * 64 + (warp & 3) * 16;
    mbar_wait(bars + 128, 0);
    const float gt0 = __ldcg(g_gate + m0 + rl + g), gt1 = __ldcg(g_gate + m0 + rl + g + 8);
    const float om0 = rbf(1.f - gt0), om1 = rbf(1.f - gt1);
    const int mi = lane >> 3, tc = wg * 8 + (warp & 3) * 2 + (mi & 1);
    const int qr = rl + 8 * (mi & 1) + (lane & 7);
#pragma unroll
    for (int j2 = 0; j2 < 8; j2++) {
      const int d = 16 * j2 + 8 * (mi >> 1) + (lane & 7);
      uint32_t yf[4], qf[4], of[4];
      asm volatile("ldmatrix.sync.aligned.m8n8.x4.trans.shared.b16 {%0,%1,%2,%3}, [%4];" : "=r"(yf[0]), "=r"(yf[1]), "=r"(yf[2]), "=r"(yf[3])
                   : "r"(ysm + (tc >> 3) * 16384 + d * 128 + (((tc & 7) ^ (d & 7)) << 4)) : "memory");
      const int cc = 2 * j2 + (mi >> 1);
      const uint32_t qa = qsm + (cc >> 3) * 16384 + qr * 128 + (((cc & 7) ^ (qr & 7)) << 4);
      asm volatile("ldmatrix.sync.aligned.m8n8.x4.shared.b16 {%0,%1,%2,%3}, [%4];" : "=r"(qf[0]), "=r"(qf[1]), "=r"(qf[2]), "=r"(qf[3]) : "r"(qa) : "memory");
#pragma unroll
      for (int jj = 0; jj < 2; jj++)
#pragma unroll
        for (int hf = 0; hf < 2; hf++) {
          const int j = 2 * j2 + jj;
          const float gt = hf ? gt1 : gt0, om = hf ? om1 : om0;
          const uint32_t aw = bmul2(qf[2 * jj + hf], yf[2 * jj + hf]);
          const uint32_t bw = pack_bf16(acc[4 * j + 2 * hf], acc[4 * j + 2 * hf + 1]);
          of[2 * jj + hf] = badd2(pack_bf16(gt * bf_lo(aw), gt * bf_hi(aw)), pack_bf16(om * bf_lo(bw), om * bf_hi(bw)));
        }
      asm volatile("stmatrix.sync.aligned.m8n8.x4.shared.b16 [%0], {%1,%2,%3,%4};" ::"r"(qa), "r"(of[0]), "r"(of[1]), "r"(of[2]), "r"(of[3]) : "memory");
    }
    fence_async_smem();
    bar_sync(1, 256);
    if (tid == 0) {
      asm volatile("cp.async.bulk.tensor.2d.global.shared::cta.bulk_group [%0, {%2, %3}], [%1];" ::"l"(&tmOut), "r"(qsm), "r"(n0), "r"(m0) : "memory");
      asm volatile("cp.async.bulk.tensor.2d.global.shared::cta.bulk_group [%0, {%2, %3}], [%1];" ::"l"(&tmOut), "r"(qsm + 16384), "r"(n0 + 64), "r"(m0) : "memory");
      asm volatile("cp.async.bulk.commit_group;\ncp.async.bulk.wait_group 0;" ::: "memory");
    }
    TS2(31);
  }
}

typedef CUresult (*PFN_encodeTiled)(CUtensorMap*, CUtensorMapDataType, cuuint32_t, void*, const cuuint64_t*, const cuuint64_t*,
                                    const cuuint32_t*, const cuuint32_t*, CUtensorMapInterleave, CUtensorMapSwizzle,
                                    CUtensorMapL2promotion, CUtensorMapFloatOOBfill);
static PFN_encodeTiled get_encode() {
  static PFN_encodeTiled fn = nullptr;
  if (!fn) {
    void* p = nullptr; cudaDriverEntryPointQueryResult st;
    cudaGetDriverEntryPoint("cuTensorMapEncodeTiled", &p, cudaEnableDefault, &st);
    fn = (PFN_encodeTiled)p;
  }
  return fn;
}
static CUtensorMap make_tm(const void* ptr, uint64_t rows, uint64_t cols, uint32_t brows, uint32_t bcols, CUtensorMapSwizzle swz = CU_TENSOR_MAP_SWIZZLE_128B) {
  CUtensorMap tm;
  cuuint64_t dims[2] = {cols, rows};
  cuuint64_t strides[1] = {cols * 2};
  cuuint32_t box[2] = {bcols, brows};
  cuuint32_t es[2] = {1, 1};
  get_encode()(&tm, CU_TENSOR_MAP_DATA_TYPE_BFLOAT16, 2, const_cast<void*>(ptr), dims, strides, box, es, CU_TENSOR_MAP_INTERLEAVE_NONE,
               swz, CU_TENSOR_MAP_L2_PROMOTION_L2_256B, CU_TENSOR_MAP_FLOAT_OOB_FILL_NONE);
  return tm;
}
static CUtensorMap make_tm_x(const void* ptr) {
  CUtensorMap tm;
  cuuint64_t dims[3] = {64, (cuuint64_t)SEQ, 16};
  cuuint64_t strides[2] = {DM * 2, 128};
  cuuint32_t box[3] = {64, SEG, 8};
  cuuint32_t es[3] = {1, 1, 1};
  get_encode()(&tm, CU_TENSOR_MAP_DATA_TYPE_BFLOAT16, 3, const_cast<void*>(ptr), dims, strides, box, es, CU_TENSOR_MAP_INTERLEAVE_NONE,
               CU_TENSOR_MAP_SWIZZLE_128B, CU_TENSOR_MAP_L2_PROMOTION_L2_256B, CU_TENSOR_MAP_FLOAT_OOB_FILL_NONE);
  return tm;
}
static CUtensorMap make_tm_kv(const void* ptr) {
  CUtensorMap tm;
  cuuint64_t dims[4] = {(cuuint64_t)DM, 2, (cuuint64_t)SEQ / 32, 16};
  cuuint64_t strides[3] = {DM * 2, DM * 2 * 32, DM * 2 * 2};
  cuuint32_t box[4] = {64, 2, 4, 16};
  cuuint32_t es[4] = {1, 1, 1, 1};
  get_encode()(&tm, CU_TENSOR_MAP_DATA_TYPE_BFLOAT16, 4, const_cast<void*>(ptr), dims, strides, box, es, CU_TENSOR_MAP_INTERLEAVE_NONE,
               CU_TENSOR_MAP_SWIZZLE_128B, CU_TENSOR_MAP_L2_PROMOTION_L2_256B, CU_TENSOR_MAP_FLOAT_OOB_FILL_NONE);
  return tm;
}
template <typename T> static T* sym_addr(T& sym) { void* p = nullptr; cudaGetSymbolAddress(&p, sym); return (T*)p; }

#define RUN(bit) true

#define K2_PDL 1
extern "C" void kernel_launch(void* const* d_in, const int* in_sizes, int n_in, void* d_out, int out_size) {
  const bf16* q = (const bf16*)d_in[0];
  const bf16* k = (const bf16*)d_in[1];
  const bf16* v = (const bf16*)d_in[2];
  const bf16* shift_k = (const bf16*)d_in[3];
  const bf16* ssm_k = (const bf16*)d_in[4];
  const bf16* ssm_D = (const bf16*)d_in[5];
  const bf16* mem0 = (const bf16*)d_in[7];
  const bf16* Wq = (const bf16*)d_in[8];
  const bf16* Wk = (const bf16*)d_in[9];
  const bf16* Wv = (const bf16*)d_in[10];
  const bf16* Wo = (const bf16*)d_in[11];
  const bf16* gate_w = (const bf16*)d_in[13];
  bf16* out = (bf16*)d_out;
  cudaStream_t st = cudaStreamPerThread;
  static cudaStream_t st2 = nullptr;
  static cudaEvent_t ev0 = nullptr, ev2 = nullptr;
  if (!st2) {
    cudaStreamCreateWithFlags(&st2, cudaStreamNonBlocking);
    cudaEventCreateWithFlags(&ev0, cudaEventDisableTiming);
    cudaEventCreateWithFlags(&ev2, cudaEventDisableTiming);
    cudaFuncSetAttribute(ka_prep, cudaFuncAttributeMaxDynamicSharedMemorySize, KA_SMEM);
    cudaFuncSetAttribute(kc_conv, cudaFuncAttributeMaxDynamicSharedMemorySize, KC_SMEM);
    cudaFuncSetAttribute(k1_rec, cudaFuncAttributeMaxDynamicSharedMemorySize, K1_SMEM);
    cudaFuncSetAttribute(k2_gemm<1>, cudaFuncAttributeMaxDynamicSharedMemorySize, G_SMEM);
  }
  void* ox = nullptr; cudaGetSymbolAddress(&ox, g_ox);
  void* y2 = nullptr; cudaGetSymbolAddress(&y2, g_y2T);
  CUtensorMap tmO = make_tm(ox, SEQ, HD, 128, 64);
  CUtensorMap tmWo = make_tm(Wo, HD, DM, 64, 64);
  CUtensorMap tmX = make_tm_x(q);
  CUtensorMap tmY = make_tm(y2, DM, SEQ, 128, 64);
  CUtensorMap tmQ = make_tm(q, SEQ, DM, 128, 64);
  CUtensorMap tmOut = make_tm(out, SEQ, DM, 128, 64);
  CUtensorMap tmWq = make_tm(Wq, DM, HD, 128, 64), tmWk = make_tm(Wk, DM, HD, 128, 64), tmWv = make_tm(Wv, DM, HD, 128, 64);
  CUtensorMap tmOx = make_tm(ox, SEQ, HD, 32, 64);
  CUtensorMap tmYo = make_tm(y2, (uint64_t)DM * 64, 32, 64, 32, CU_TENSOR_MAP_SWIZZLE_64B);
  CUtensorMap tmK = make_tm_kv(k), tmV = make_tm_kv(v);
  void* xw = nullptr; cudaGetSymbolAddress(&xw, g_xw);
  xw = (void*)(((uintptr_t)xw + (2u << 20) - 1) & ~(uintptr_t)((2u << 20) - 1));
  cudaEventRecord(ev0, st);
  cudaStreamWaitEvent(st2, ev0, 0);
  if (RUN(4)) k1_rec<<<128, 256, K1_SMEM, st>>>(tmX, tmWq, tmWk, tmWv, tmOx, (uint8_t*)xw, mem0, Wo);
  if (RUN(4)) k1_rec<<<4, 256, K1_SMEM, st2>>>(tmX, tmWq, tmWk, tmWv, tmOx, (uint8_t*)xw + XW_DRY, mem0, Wo);
  if (RUN(1)) ka_prep<<<4, 512, KA_SMEM, st2>>>(tmK, tmV, q, gate_w, shift_k);
  if (RUN(16)) kc_conv<<<4, 512, KC_SMEM, st2>>>(tmYo, ssm_k, ssm_D);
  if (RUN(8)) {
    cudaLaunchConfig_t cfg = {};
    cfg.gridDim = dim3(DM / 128, SEQ / 128); cfg.blockDim = dim3(544); cfg.dynamicSmemBytes = G_SMEM; cfg.stream = st;
    cudaLaunchAttribute at[1];
    at[0].id = cudaLaunchAttributeProgrammaticStreamSerialization; at[0].val.programmaticStreamSerializationAllowed = K2_PDL;
    cfg.attrs = at; cfg.numAttrs = 1;
    cudaLaunchKernelEx(&cfg, k2_gemm<1>, tmO, tmWo, tmY, tmQ, tmOut, tmYo, ssm_k, ssm_D, HD / 64);
  }
  cudaEventRecord(ev2, st2);
  cudaStreamWaitEvent(st, ev2, 0);
}
```

```cpp
#include <cuda_runtime.h>
#include <cuda_bf16.h>
#include <cuda.h>
#include <stdint.h>
#include <string.h>

typedef __nv_bfloat16 bf16;

constexpr int SEQ = 2048, DM = 1024, NH = 32, DH = 128, HD = NH * DH, MEM = 8, SEG = 32, NSEG = SEQ / SEG;

__device__ __forceinline__ uint32_t smem_u32(const void* p) { return (uint32_t)__cvta_generic_to_shared(p); }
__device__ __forceinline__ void wg_fence() { asm volatile("wgmma.fence.sync.aligned;\n" ::: "memory"); }
__device__ __forceinline__ void wg_commit() { asm volatile("wgmma.commit_group.sync.aligned;\n" ::: "memory"); }
template <int N> __device__ __forceinline__ void wg_wait() { asm volatile("wgmma.wait_group.sync.aligned %0;\n" ::"n"(N) : "memory"); }
template <int N> __device__ __forceinline__ void fence_regs(float (&a)[N]) {
#pragma unroll
  for (int i = 0; i < N; i++) asm volatile("" : "+f"(a[i])::"memory");
}
__device__ __forceinline__ void fence_async_smem() { asm volatile("fence.proxy.async.shared::cta;\n" ::: "memory"); }
__device__ __forceinline__ void bar_sync(int id, int n) { asm volatile("bar.sync %0, %1;" ::"r"(id), "r"(n) : "memory"); }
__device__ __forceinline__ void bar_arrive(int id, int n) { asm volatile("bar.arrive %0, %1;" ::"r"(id), "r"(n) : "memory"); }
__device__ __forceinline__ uint64_t make_desc(uint32_t addr, uint32_t lbo, uint32_t sbo, uint32_t swz) {
  return (uint64_t)((addr & 0x3FFFF) >> 4) | ((uint64_t)((lbo & 0x3FFFF) >> 4) << 16) | ((uint64_t)((sbo & 0x3FFFF) >> 4) << 32) | ((uint64_t)swz << 62);
}
__device__ __forceinline__ void mbar_init(uint32_t bar, int cnt) { asm volatile("mbarrier.init.shared::cta.b64 [%0], %1;" ::"r"(bar), "r"(cnt) : "memory"); }
__device__ __forceinline__ void mbar_expect_tx(uint32_t bar, uint32_t bytes) {
  asm volatile("mbarrier.arrive.expect_tx.shared::cta.b64 _, [%0], %1;" ::"r"(bar), "r"(bytes) : "memory");
}
__device__ __forceinline__ void mbar_arrive(uint32_t bar) { asm volatile("mbarrier.arrive.shared::cta.b64 _, [%0];" ::"r"(bar) : "memory"); }
__device__ __forceinline__ bool mbar_try(uint32_t bar, uint32_t parity) {
  uint32_t ok;
  asm volatile("{\n.reg .pred p;\nmbarrier.try_wait.parity.shared::cta.b64 p, [%1], %2;\nselp.u32 %0, 1, 0, p;\n}" : "=r"(ok) : "r"(bar), "r"(parity) : "memory");
  return ok != 0;
}
__device__ __forceinline__ void mbar_wait(uint32_t bar, uint32_t parity) {
  for (int i = 0; i < (1 << 22); i++) if (mbar_try(bar, parity)) return;
}
__device__ __forceinline__ void tma_load_2d(uint32_t dst, const CUtensorMap* tm, int c0, int c1, uint32_t bar) {
  asm volatile("cp.async.bulk.tensor.2d.shared::cluster.global.mbarrier::complete_tx::bytes [%0], [%1, {%3, %4}], [%2];"
               ::"r"(dst), "l"(tm), "r"(bar), "r"(c0), "r"(c1) : "memory");
}
__device__ __forceinline__ void tma_load_2d_mc(uint32_t dst, const CUtensorMap* tm, int c0, int c1, uint32_t bar, uint16_t mask) {
  asm volatile("cp.async.bulk.tensor.2d.shared::cluster.global.mbarrier::complete_tx::bytes.multicast::cluster [%0], [%1, {%3, %4}], [%2], %5;"
               ::"r"(dst), "l"(tm), "r"(bar), "r"(c0), "r"(c1), "h"(mask) : "memory");
}
__device__ __forceinline__ uint32_t pack_bf16(float lo, float hi) {
  uint32_t r; asm("cvt.rn.bf16x2.f32 %0, %1, %2;" : "=r"(r) : "f"(hi), "f"(lo)); return r;
}
__device__ __forceinline__ float bf_lo(uint32_t w) { return __uint_as_float(w << 16); }
__device__ __forceinline__ float bf_hi(uint32_t w) { return __uint_as_float(w & 0xffff0000u); }
__device__ __forceinline__ float rbf(float x) { return __bfloat162float(__float2bfloat16_rn(x)); }
__device__ __forceinline__ uint32_t prmt(uint32_t a, uint32_t b, uint32_t sel) { uint32_t r; asm("prmt.b32 %0, %1, %2, %3;" : "=r"(r) : "r"(a), "r"(b), "r"(sel)); return r; }
__device__ __forceinline__ uint4 ldg_nc_v4(const void* p) {
  uint4 v; asm volatile("ld.global.nc.L1::no_allocate.v4.u32 {%0,%1,%2,%3}, [%4];" : "=r"(v.x), "=r"(v.y), "=r"(v.z), "=r"(v.w) : "l"(p)); return v;
}
__device__ __forceinline__ void sts_v4(uint32_t a, uint4 v) { asm volatile("st.shared.v4.u32 [%0], {%1,%2,%3,%4};" ::"r"(a), "r"(v.x), "r"(v.y), "r"(v.z), "r"(v.w) : "memory"); }
__device__ __forceinline__ uint4 lds_v4(uint32_t a) { uint4 v; asm volatile("ld.shared.v4.u32 {%0,%1,%2,%3}, [%4];" : "=r"(v.x), "=r"(v.y), "=r"(v.z), "=r"(v.w) : "r"(a) : "memory"); return v; }
__device__ __forceinline__ uint32_t lds_u32(uint32_t a) { uint32_t v; asm volatile("ld.shared.u32 %0, [%1];" : "=r"(v) : "r"(a) : "memory"); return v; }
__device__ __forceinline__ void sts_u32(uint32_t a, uint32_t v) { asm volatile("st.shared.u32 [%0], %1;" ::"r"(a), "r"(v) : "memory"); }

template<int OFF, int NT> __device__ __forceinline__ void wg_rs_n8(float (&d)[NT], uint32_t a0, uint32_t a1, uint32_t a2, uint32_t a3, uint64_t db, int sd) {
  asm volatile("{\n.reg .pred p;\nsetp.ne.b32 p, %9, 0;\n"
    "wgmma.mma_async.sync.aligned.m64n8k16.f32.bf16.bf16 {%0, %1, %2, %3}, {%4, %5, %6, %7}, %8, p, 1, 1, 0;\n}\n"
    : "+f"(d[OFF + 0]), "+f"(d[OFF + 1]), "+f"(d[OFF + 2]), "+f"(d[OFF + 3]) : "r"(a0), "r"(a1), "r"(a2), "r"(a3), "l"(db), "r"(sd));
}
template<int OFF, int NT> __device__ __forceinline__ void wg_rs_n16(float (&d)[NT], uint32_t a0, uint32_t a1, uint32_t a2, uint32_t a3, uint64_t db, int sd) {
  asm volatile("{\n.reg .pred p;\nsetp.ne.b32 p, %13, 0;\n"
    "wgmma.mma_async.sync.aligned.m64n16k16.f32.bf16.bf16 {%0, %1, %2, %3, %4, %5, %6, %7}, {%8, %9, %10, %11}, %12, p, 1, 1, 0;\n}\n"
    : "+f"(d[OFF + 0]), "+f"(d[OFF + 1]), "+f"(d[OFF + 2]), "+f"(d[OFF + 3]), "+f"(d[OFF + 4]), "+f"(d[OFF + 5]), "+f"(d[OFF + 6]), "+f"(d[OFF + 7]) : "r"(a0), "r"(a1), "r"(a2), "r"(a3), "l"(db), "r"(sd));
}
template<int OFF, int NT> __device__ __forceinline__ void wg_rs_n24(float (&d)[NT], uint32_t a0, uint32_t a1, uint32_t a2, uint32_t a3, uint64_t db, int sd) {
  asm volatile("{\n.reg .pred p;\nsetp.ne.b32 p, %17, 0;\n"
    "wgmma.mma_async.sync.aligned.m64n24k16.f32.bf16.bf16 {%0, %1, %2, %3, %4, %5, %6, %7, %8, %9, %10, %11}, {%12, %13, %14, %15}, %16, p, 1, 1, 0;\n}\n"
    : "+f"(d[OFF + 0]), "+f"(d[OFF + 1]), "+f"(d[OFF + 2]), "+f"(d[OFF + 3]), "+f"(d[OFF + 4]), "+f"(d[OFF + 5]), "+f"(d[OFF + 6]), "+f"(d[OFF + 7]), "+f"(d[OFF + 8]), "+f"(d[OFF + 9]), "+f"(d[OFF + 10]), "+f"(d[OFF + 11]) : "r"(a0), "r"(a1), "r"(a2), "r"(a3), "l"(db), "r"(sd));
}
template<int OFF, int NT> __device__ __forceinline__ void wg_rs_n32(float (&d)[NT], uint32_t a0, uint32_t a1, uint32_t a2, uint32_t a3, uint64_t db, int sd) {
  asm volatile("{\n.reg .pred p;\nsetp.ne.b32 p, %21, 0;\n"
    "wgmma.mma_async.sync.aligned.m64n32k16.f32.bf16.bf16 {%0, %1, %2, %3, %4, %5, %6, %7, %8, %9, %10, %11, %12, %13, %14, %15}, {%16, %17, %18, %19}, %20, p, 1, 1, 0;\n}\n"
    : "+f"(d[OFF + 0]), "+f"(d[OFF + 1]), "+f"(d[OFF + 2]), "+f"(d[OFF + 3]), "+f"(d[OFF + 4]), "+f"(d[OFF + 5]), "+f"(d[OFF + 6]), "+f"(d[OFF + 7]), "+f"(d[OFF + 8]), "+f"(d[OFF + 9]), "+f"(d[OFF + 10]), "+f"(d[OFF + 11]), "+f"(d[OFF + 12]), "+f"(d[OFF + 13]), "+f"(d[OFF + 14]), "+f"(d[OFF + 15]) : "r"(a0), "r"(a1), "r"(a2), "r"(a3), "l"(db), "r"(sd));
}
template<int OFF, int NT> __device__ __forceinline__ void wg_rs_n40(float (&d)[NT], uint32_t a0, uint32_t a1, uint32_t a2, uint32_t a3, uint64_t db, int sd) {
  asm volatile("{\n.reg .pred p;\nsetp.ne.b32 p, %25, 0;\n"
    "wgmma.mma_async.sync.aligned.m64n40k16.f32.bf16.bf16 {%0, %1, %2, %3, %4, %5, %6, %7, %8, %9, %10, %11, %12, %13, %14, %15, %16, %17, %18, %19}, {%20, %21, %22, %23}, %24, p, 1, 1, 0;\n}\n"
    : "+f"(d[OFF + 0]), "+f"(d[OFF + 1]), "+f"(d[OFF + 2]), "+f"(d[OFF + 3]), "+f"(d[OFF + 4]), "+f"(d[OFF + 5]), "+f"(d[OFF + 6]), "+f"(d[OFF + 7]), "+f"(d[OFF + 8]), "+f"(d[OFF + 9]), "+f"(d[OFF + 10]), "+f"(d[OFF + 11]), "+f"(d[OFF + 12]), "+f"(d[OFF + 13]), "+f"(d[OFF + 14]), "+f"(d[OFF + 15]), "+f"(d[OFF + 16]), "+f"(d[OFF + 17]), "+f"(d[OFF + 18]), "+f"(d[OFF + 19]) : "r"(a0), "r"(a1), "r"(a2), "r"(a3), "l"(db), "r"(sd));
}
template<int OFF, int NT> __device__ __forceinline__ void wg_rs_n48(float (&d)[NT], uint32_t a0, uint32_t a1, uint32_t a2, uint32_t a3, uint64_t db, int sd) {
  asm volatile("{\n.reg .pred p;\nsetp.ne.b32 p, %29, 0;\n"
    "wgmma.mma_async.sync.aligned.m64n48k16.f32.bf16.bf16 {%0, %1, %2, %3, %4, %5, %6, %7, %8, %9, %10, %11, %12, %13, %14, %15, %16, %17, %18, %19, %20, %21, %22, %23}, {%24, %25, %26, %27}, %28, p, 1, 1, 0;\n}\n"
    : "+f"(d[OFF + 0]), "+f"(d[OFF + 1]), "+f"(d[OFF + 2]), "+f"(d[OFF + 3]), "+f"(d[OFF + 4]), "+f"(d[OFF + 5]), "+f"(d[OFF + 6]), "+f"(d[OFF + 7]), "+f"(d[OFF + 8]), "+f"(d[OFF + 9]), "+f"(d[OFF + 10]), "+f"(d[OFF + 11]), "+f"(d[OFF + 12]), "+f"(d[OFF + 13]), "+f"(d[OFF + 14]), "+f"(d[OFF + 15]), "+f"(d[OFF + 16]), "+f"(d[OFF + 17]), "+f"(d[OFF + 18]), "+f"(d[OFF + 19]), "+f"(d[OFF + 20]), "+f"(d[OFF + 21]), "+f"(d[OFF + 22]), "+f"(d[OFF + 23]) : "r"(a0), "r"(a1), "r"(a2), "r"(a3), "l"(db), "r"(sd));
}
template<int OFF, int NT> __device__ __forceinline__ void wg_rs_n56(float (&d)[NT], uint32_t a0, uint32_t a1, uint32_t a2, uint32_t a3, uint64_t db, int sd) {
  asm volatile("{\n.reg .pred p;\nsetp.ne.b32 p, %33, 0;\n"
    "wgmma.mma_async.sync.aligned.m64n56k16.f32.bf16.bf16 {%0, %1, %2, %3, %4, %5, %6, %7, %8, %9, %10, %11, %12, %13, %14, %15, %16, %17, %18, %19, %20, %21, %22, %23, %24, %25, %26, %27}, {%28, %29, %30, %31}, %32, p, 1, 1, 0;\n}\n"
    : "+f"(d[OFF + 0]), "+f"(d[OFF + 1]), "+f"(d[OFF + 2]), "+f"(d[OFF + 3]), "+f"(d[OFF + 4]), "+f"(d[OFF + 5]), "+f"(d[OFF + 6]), "+f"(d[OFF + 7]), "+f"(d[OFF + 8]), "+f"(d[OFF + 9]), "+f"(d[OFF + 10]), "+f"(d[OFF + 11]), "+f"(d[OFF + 12]), "+f"(d[OFF + 13]), "+f"(d[OFF + 14]), "+f"(d[OFF + 15]), "+f"(d[OFF + 16]), "+f"(d[OFF + 17]), "+f"(d[OFF + 18]), "+f"(d[OFF + 19]), "+f"(d[OFF + 20]), "+f"(d[OFF + 21]), "+f"(d[OFF + 22]), "+f"(d[OFF + 23]), "+f"(d[OFF + 24]), "+f"(d[OFF + 25]), "+f"(d[OFF + 26]), "+f"(d[OFF + 27]) : "r"(a0), "r"(a1), "r"(a2), "r"(a3), "l"(db), "r"(sd));
}
template<int OFF, int NT> __device__ __forceinline__ void wg_rs_n64(float (&d)[NT], uint32_t a0, uint32_t a1, uint32_t a2, uint32_t a3, uint64_t db, int sd) {
  asm volatile("{\n.reg .pred p;\nsetp.ne.b32 p, %37, 0;\n"
    "wgmma.mma_async.sync.aligned.m64n64k16.f32.bf16.bf16 {%0, %1, %2, %3, %4, %5, %6, %7, %8, %9, %10, %11, %12, %13, %14, %15, %16, %17, %18, %19, %20, %21, %22, %23, %24, %25, %26, %27, %28, %29, %30, %31}, {%32, %33, %34, %35}, %36, p, 1, 1, 0;\n}\n"
    : "+f"(d[OFF + 0]), "+f"(d[OFF + 1]), "+f"(d[OFF + 2]), "+f"(d[OFF + 3]), "+f"(d[OFF + 4]), "+f"(d[OFF + 5]), "+f"(d[OFF + 6]), "+f"(d[OFF + 7]), "+f"(d[OFF + 8]), "+f"(d[OFF + 9]), "+f"(d[OFF + 10]), "+f"(d[OFF + 11]), "+f"(d[OFF + 12]), "+f"(d[OFF + 13]), "+f"(d[OFF + 14]), "+f"(d[OFF + 15]), "+f"(d[OFF + 16]), "+f"(d[OFF + 17]), "+f"(d[OFF + 18]), "+f"(d[OFF + 19]), "+f"(d[OFF + 20]), "+f"(d[OFF + 21]), "+f"(d[OFF + 22]), "+f"(d[OFF + 23]), "+f"(d[OFF + 24]), "+f"(d[OFF + 25]), "+f"(d[OFF + 26]), "+f"(d[OFF + 27]), "+f"(d[OFF + 28]), "+f"(d[OFF + 29]), "+f"(d[OFF + 30]), "+f"(d[OFF + 31]) : "r"(a0), "r"(a1), "r"(a2), "r"(a3), "l"(db), "r"(sd));
}
template<int OFF, int NT> __device__ __forceinline__ void wg_rs_n8_tb(float (&d)[NT], uint32_t a0, uint32_t a1, uint32_t a2, uint32_t a3, uint64_t db, int sd) {
  asm volatile("{\n.reg .pred p;\nsetp.ne.b32 p, %9, 0;\n"
    "wgmma.mma_async.sync.aligned.m64n8k16.f32.bf16.bf16 {%0, %1, %2, %3}, {%4, %5, %6, %7}, %8, p, 1, 1, 1;\n}\n"
    : "+f"(d[OFF + 0]), "+f"(d[OFF + 1]), "+f"(d[OFF + 2]), "+f"(d[OFF + 3]) : "r"(a0), "r"(a1), "r"(a2), "r"(a3), "l"(db), "r"(sd));
}
template<int OFF, int NT> __device__ __forceinline__ void wg_rs_n16_tb(float (&d)[NT], uint32_t a0, uint32_t a1, uint32_t a2, uint32_t a3, uint64_t db, int sd) {
  asm volatile("{\n.reg .pred p;\nsetp.ne.b32 p, %13, 0;\n"
    "wgmma.mma_async.sync.aligned.m64n16k16.f32.bf16.bf16 {%0, %1, %2, %3, %4, %5, %6, %7}, {%8, %9, %10, %11}, %12, p, 1, 1, 1;\n}\n"
    : "+f"(d[OFF + 0]), "+f"(d[OFF + 1]), "+f"(d[OFF + 2]), "+f"(d[OFF + 3]), "+f"(d[OFF + 4]), "+f"(d[OFF + 5]), "+f"(d[OFF + 6]), "+f"(d[OFF + 7]) : "r"(a0), "r"(a1), "r"(a2), "r"(a3), "l"(db), "r"(sd));
}
template<int OFF, int NT> __device__ __forceinline__ void wg_ss_n16_ta_tb(float (&d)[NT], uint64_t da, uint64_t db, int sd) {
  asm volatile("{\n.reg .pred p;\nsetp.ne.b32 p, %10, 0;\n"
    "wgmma.mma_async.sync.aligned.m64n16k16.f32.bf16.bf16 {%0, %1, %2, %3, %4, %5, %6, %7}, %8, %9, p, 1, 1, 1, 1;\n}\n"
    : "+f"(d[OFF + 0]), "+f"(d[OFF + 1]), "+f"(d[OFF + 2]), "+f"(d[OFF + 3]), "+f"(d[OFF + 4]), "+f"(d[OFF + 5]), "+f"(d[OFF + 6]), "+f"(d[OFF + 7]) : "l"(da), "l"(db), "r"(sd));
}
template<int OFF, int NT> __device__ __forceinline__ void wg_ss_n64_ta(float (&d)[NT], uint64_t da, uint64_t db, int sd) {
  asm volatile("{\n.reg .pred p;\nsetp.ne.b32 p, %34, 0;\n"
    "wgmma.mma_async.sync.aligned.m64n64k16.f32.bf16.bf16 {%0, %1, %2, %3, %4, %5, %6, %7, %8, %9, %10, %11, %12, %13, %14, %15, %16, %17, %18, %19, %20, %21, %22, %23, %24, %25, %26, %27, %28, %29, %30, %31}, %32, %33, p, 1, 1, 1, 0;\n}\n"
    : "+f"(d[OFF + 0]), "+f"(d[OFF + 1]), "+f"(d[OFF + 2]), "+f"(d[OFF + 3]), "+f"(d[OFF + 4]), "+f"(d[OFF + 5]), "+f"(d[OFF + 6]), "+f"(d[OFF + 7]), "+f"(d[OFF + 8]), "+f"(d[OFF + 9]), "+f"(d[OFF + 10]), "+f"(d[OFF + 11]), "+f"(d[OFF + 12]), "+f"(d[OFF + 13]), "+f"(d[OFF + 14]), "+f"(d[OFF + 15]), "+f"(d[OFF + 16]), "+f"(d[OFF + 17]), "+f"(d[OFF + 18]), "+f"(d[OFF + 19]), "+f"(d[OFF + 20]), "+f"(d[OFF + 21]), "+f"(d[OFF + 22]), "+f"(d[OFF + 23]), "+f"(d[OFF + 24]), "+f"(d[OFF + 25]), "+f"(d[OFF + 26]), "+f"(d[OFF + 27]), "+f"(d[OFF + 28]), "+f"(d[OFF + 29]), "+f"(d[OFF + 30]), "+f"(d[OFF + 31]) : "l"(da), "l"(db), "r"(sd));
}
template<int OFF, int NT> __device__ __forceinline__ void wg_ss_n8_ta(float (&d)[NT], uint64_t da, uint64_t db, int sd) {
  asm volatile("{\n.reg .pred p;\nsetp.ne.b32 p, %6, 0;\n"
    "wgmma.mma_async.sync.aligned.m64n8k16.f32.bf16.bf16 {%0, %1, %2, %3}, %4, %5, p, 1, 1, 1, 0;\n}\n"
    : "+f"(d[OFF + 0]), "+f"(d[OFF + 1]), "+f"(d[OFF + 2]), "+f"(d[OFF + 3]) : "l"(da), "l"(db), "r"(sd));
}
template<int OFF, int NT> __device__ __forceinline__ void wg_ss_n128_tb(float (&d)[NT], uint64_t da, uint64_t db, int sd) {
  asm volatile("{\n.reg .pred p;\nsetp.ne.b32 p, %66, 0;\n"
    "wgmma.mma_async.sync.aligned.m64n128k16.f32.bf16.bf16 {%0, %1, %2, %3, %4, %5, %6, %7, %8, %9, %10, %11, %12, %13, %14, %15, %16, %17, %18, %19, %20, %21, %22, %23, %24, %25, %26, %27, %28, %29, %30, %31, %32, %33, %34, %35, %36, %37, %38, %39, %40, %41, %42, %43, %44, %45, %46, %47, %48, %49, %50, %51, %52, %53, %54, %55, %56, %57, %58, %59, %60, %61, %62, %63}, %64, %65, p, 1, 1, 0, 1;\n}\n"
    : "+f"(d[OFF + 0]), "+f"(d[OFF + 1]), "+f"(d[OFF + 2]), "+f"(d[OFF + 3]), "+f"(d[OFF + 4]), "+f"(d[OFF + 5]), "+f"(d[OFF + 6]), "+f"(d[OFF + 7]), "+f"(d[OFF + 8]), "+f"(d[OFF + 9]), "+f"(d[OFF + 10]), "+f"(d[OFF + 11]), "+f"(d[OFF + 12]), "+f"(d[OFF + 13]), "+f"(d[OFF + 14]), "+f"(d[OFF + 15]), "+f"(d[OFF + 16]), "+f"(d[OFF + 17]), "+f"(d[OFF + 18]), "+f"(d[OFF + 19]), "+f"(d[OFF + 20]), "+f"(d[OFF + 21]), "+f"(d[OFF + 22]), "+f"(d[OFF + 23]), "+f"(d[OFF + 24]), "+f"(d[OFF + 25]), "+f"(d[OFF + 26]), "+f"(d[OFF + 27]), "+f"(d[OFF + 28]), "+f"(d[OFF + 29]), "+f"(d[OFF + 30]), "+f"(d[OFF + 31]), "+f"(d[OFF + 32]), "+f"(d[OFF + 33]), "+f"(d[OFF + 34]), "+f"(d[OFF + 35]), "+f"(d[OFF + 36]), "+f"(d[OFF + 37]), "+f"(d[OFF + 38]), "+f"(d[OFF + 39]), "+f"(d[OFF + 40]), "+f"(d[OFF + 41]), "+f"(d[OFF + 42]), "+f"(d[OFF + 43]), "+f"(d[OFF + 44]), "+f"(d[OFF + 45]), "+f"(d[OFF + 46]), "+f"(d[OFF + 47]), "+f"(d[OFF + 48]), "+f"(d[OFF + 49]), "+f"(d[OFF + 50]), "+f"(d[OFF + 51]), "+f"(d[OFF + 52]), "+f"(d[OFF + 53]), "+f"(d[OFF + 54]), "+f"(d[OFF + 55]), "+f"(d[OFF + 56]), "+f"(d[OFF + 57]), "+f"(d[OFF + 58]), "+f"(d[OFF + 59]), "+f"(d[OFF + 60]), "+f"(d[OFF + 61]), "+f"(d[OFF + 62]), "+f"(d[OFF + 63]) : "l"(da), "l"(db), "r"(sd));
}
template<int OFF, int NT> __device__ __forceinline__ void wg_ss_n8_ta_tb(float (&d)[NT], uint64_t da, uint64_t db, int sd) {
  asm volatile("{\n.reg .pred p;\nsetp.ne.b32 p, %6, 0;\n"
    "wgmma.mma_async.sync.aligned.m64n8k16.f32.bf16.bf16 {%0, %1, %2, %3}, %4, %5, p, 1, 1, 1, 1;\n}\n"
    : "+f"(d[OFF + 0]), "+f"(d[OFF + 1]), "+f"(d[OFF + 2]), "+f"(d[OFF + 3]) : "l"(da), "l"(db), "r"(sd));
}
template<int OFF, int NT> __device__ __forceinline__ void wg_ss_n32_ta(float (&d)[NT], uint64_t da, uint64_t db, int sd) {
  asm volatile("{\n.reg .pred p;\nsetp.ne.b32 p, %18, 0;\n"
    "wgmma.mma_async.sync.aligned.m64n32k16.f32.bf16.bf16 {%0, %1, %2, %3, %4, %5, %6, %7, %8, %9, %10, %11, %12, %13, %14, %15}, %16, %17, p, 1, 1, 1, 0;\n}\n"
    : "+f"(d[OFF + 0]), "+f"(d[OFF + 1]), "+f"(d[OFF + 2]), "+f"(d[OFF + 3]), "+f"(d[OFF + 4]), "+f"(d[OFF + 5]), "+f"(d[OFF + 6]), "+f"(d[OFF + 7]), "+f"(d[OFF + 8]), "+f"(d[OFF + 9]), "+f"(d[OFF + 10]), "+f"(d[OFF + 11]), "+f"(d[OFF + 12]), "+f"(d[OFF + 13]), "+f"(d[OFF + 14]), "+f"(d[OFF + 15]) : "l"(da), "l"(db), "r"(sd));
}

__device__ float g_gate[SEQ];
__device__ bf16 g_ox[SEQ * HD];

__device__ uint4 g_kvT[DM * 256];
__device__ unsigned g_ka_done, g_conv_done, g_k2_seen;
#define KC_BG 512
__device__ bf16 g_y2T[DM * SEQ];

constexpr int KC_UL = 73 * 16;
constexpr int KC_U = 4 * KC_UL;
constexpr int KC_K = 2080 * 4;
constexpr int KC_BUF = KC_U + KC_K;
constexpr int KC_EX = 4096, KC_BAR = KC_EX + 8192, KC_IN = KC_BAR + 64;
constexpr int KC_WG = 38912;
constexpr int KC_SMEM = 4 * KC_WG;
static_assert(KC_IN + 2 * KC_BUF <= KC_WG && KC_WG % 1024 == 0 && KC_IN + KC_BUF <= 32768, "kc smem");

__device__ __forceinline__ uint32_t bmul2(uint32_t a, uint32_t b) { uint32_t r; asm("mul.rn.bf16x2 %0, %1, %2;" : "=r"(r) : "r"(a), "r"(b)); return r; }
__device__ __forceinline__ uint32_t badd2(uint32_t a, uint32_t b) { uint32_t r; asm("add.rn.bf16x2 %0, %1, %2;" : "=r"(r) : "r"(a), "r"(b)); return r; }
__device__ __forceinline__ void cp_async16(uint32_t dst, const void* src) { asm volatile("cp.async.cg.shared.global [%0], [%1], 16;" ::"r"(dst), "l"(src) : "memory"); }

template <int G> __device__ __forceinline__ void kc_lda(uint32_t (&w)[17], uint32_t ka) {
#pragma unroll
  for (int i = 0; i < 17; i++) w[i] = lds_u32(ka + (16 * (16 * (G >> 1) + 4 * (G & 1)) - 12 + 4 * i) * 4);
}
template <bool PIPE, int G, int GN, int NA> __device__ __forceinline__ void kc_group(float (&acc)[NA], const uint32_t (&w)[17], uint32_t (&wn)[17], uint32_t ka, uint64_t db) {
  constexpr int D0 = 16 * (G >> 1) + 4 * (G & 1);
  wg_fence();
#pragma unroll
  for (int d = 0; d < 4; d++) {
    const uint64_t d0 = db + (D0 + d), d1 = d0 + ((2 * KC_UL) >> 4);
    const uint32_t* x = w + 4 * d;
    if constexpr (NA == 32) { wg_rs_n64<0>(acc, x[3], x[4], x[2], x[3], d0, 1); wg_rs_n64<0>(acc, x[1], x[2], x[0], x[1], d1, 1); }
    if constexpr (NA == 24) { wg_rs_n48<0>(acc, x[3], x[4], x[2], x[3], d0, 1); wg_rs_n48<0>(acc, x[1], x[2], x[0], x[1], d1, 1); }
    if constexpr (NA == 16) { wg_rs_n32<0>(acc, x[3], x[4], x[2], x[3], d0, 1); wg_rs_n32<0>(acc, x[1], x[2], x[0], x[1], d1, 1); }
    if constexpr (NA == 8) { wg_rs_n16<0>(acc, x[3], x[4], x[2], x[3], d0, (G & 1) | d); wg_rs_n16<0>(acc, x[1], x[2], x[0], x[1], d1, 1); }
  }
  wg_commit();
  if constexpr (PIPE && GN >= 0) kc_lda<GN>(wn, ka);
  wg_wait<0>();
  fence_regs(acc);
  if constexpr (!PIPE && GN >= 0) kc_lda<GN>(wn, ka);
}
template <int N> __device__ __forceinline__ void kc_widen(float (&o)[N + 8], const float (&a)[N], float zero) {
#pragma unroll
  for (int i = 0; i < N; i++) o[i] = a[i] + zero;
#pragma unroll
  for (int i = 0; i < 8; i++) asm volatile("add.f32 %0, %1, %1;" : "=f"(o[N + i]) : "f"(zero));
}
template <bool PIPE> __device__ __forceinline__ void kc_mma(float (&a32)[32], uint32_t ka, uint64_t db, float zero) {
  float a8[8], a16[16], a24[24];
  uint32_t w0[17], w1[17];
  kc_lda<6>(w0, ka);
  kc_group<PIPE, 6, 7>(a8, w0, w1, ka, db); kc_group<PIPE, 7, 4>(a8, w1, w0, ka, db);
  kc_widen(a16, a8, zero);
  kc_group<PIPE, 4, 5>(a16, w0, w1, ka, db); kc_group<PIPE, 5, 2>(a16, w1, w0, ka, db);
  kc_widen(a24, a16, zero);
  kc_group<PIPE, 2, 3>(a24, w0, w1, ka, db); kc_group<PIPE, 3, 0>(a24, w1, w0, ka, db);
  kc_widen(a32, a24, zero);
  kc_group<PIPE, 0, 1>(a32, w0, w1, ka, db); kc_group<PIPE, 1, -1>(a32, w1, w0, ka, db);
}
template <int HI> __device__ __forceinline__ void kc_finish(float (&acc)[32], uint32_t ex, uint32_t ua, uint32_t oa, uint32_t D2, int barid) {
  constexpr int S0 = HI ? 4 : 16;
#pragma unroll
  for (int i = 0; i < 4; i++)
    sts_v4(ex + i * 512, make_uint4(__float_as_uint(acc[S0 + 4 * i]), __float_as_uint(acc[S0 + 4 * i + 1]), __float_as_uint(acc[S0 + 4 * i + 2]), __float_as_uint(acc[S0 + 4 * i + 3])));
  bar_sync(barid, 128);
#pragma unroll
  for (int p = 0; p < 2; p++) {
    uint32_t u[4], o[4];
    asm volatile("ldmatrix.sync.aligned.m8n8.x4.trans.shared.b16 {%0,%1,%2,%3}, [%4];" : "=r"(u[0]), "=r"(u[1]), "=r"(u[2]), "=r"(u[3]) : "r"(ua + p * 256) : "memory");
#pragma unroll
    for (int q = 0; q < 2; q++) {
      const int i = 2 * p + q, o0 = HI ? 20 + 4 * i : 4 * i;
      const uint4 x = lds_v4(ex + (HI ? -4096 : 4096) + i * 512);
      float y[4] = {__uint_as_float(x.x), __uint_as_float(x.y), __uint_as_float(x.z), __uint_as_float(x.w)};
      if (o0 < 32) {
#pragma unroll
        for (int e = 0; e < 4; e++) y[e] += acc[o0 < 32 ? o0 + e : 0];
      }
      o[2 * q] = badd2(pack_bf16(y[0], y[1]), bmul2(u[2 * q], D2));
      o[2 * q + 1] = badd2(pack_bf16(y[2], y[3]), bmul2(u[2 * q + 1], D2));
    }
    asm volatile("stmatrix.sync.aligned.m8n8.x4.trans.shared.b16 [%0], {%1,%2,%3,%4};" ::"r"(oa - p * 1024), "r"(o[0]), "r"(o[1]), "r"(o[2]), "r"(o[3]) : "memory");
  }
}

__device__ __forceinline__ void wait_count(const unsigned* p, unsigned n) {
#pragma unroll 1
  for (int it = 0; it < 4000000; it++) {
    unsigned v; asm volatile("ld.acquire.gpu.global.u32 %0, [%1];" : "=r"(v) : "l"(p) : "memory");
    if (v >= n) break;
    __nanosleep(200);
  }
  asm volatile("fence.proxy.async;" ::: "memory");
}
template <int NB> __device__ __forceinline__ void conv_wg(uint32_t wb, int barid, int ch, int step, int ch1, const CUtensorMap* tmY, const bf16* __restrict__ ssm_k,
                                                          const bf16* __restrict__ ssm_D) {
  const int t128 = threadIdx.x & 127, lane = t128 & 31, wq = t128 >> 5, g = lane >> 2, tq = lane & 3, mi = lane >> 3, r8 = lane & 7;
  const uint32_t bar = wb + KC_BAR;
  if (t128 == 0) { mbar_init(bar, 1); mbar_init(bar + 8, 1); asm volatile("fence.mbarrier_init.release.cluster;" ::: "memory"); }
  if (t128 < 32 * NB) sts_v4(wb + KC_IN + (t128 >> 5) * KC_BUF + ((t128 >> 3) & 3) * KC_UL + (64 + r8) * 16, make_uint4(0, 0, 0, 0));
  else if (t128 >= 64 && t128 < 64 + 8 * NB) sts_v4(wb + KC_IN + ((t128 >> 3) & 1) * KC_BUF + KC_U + ((t128 >> 2) & 1) * 4160 + (t128 & 3) * 16, make_uint4(0, 0, 0, 0));
  uint4 kw[2]; uint32_t pw[2];
  auto fetch_u = [&](int ch, int b) {
    if (t128 == 0) {
      mbar_expect_tx(bar + 8 * b, 4096);
#pragma unroll
      for (int c = 0; c < 4; c++)
        asm volatile("cp.async.bulk.shared::cluster.global.mbarrier::complete_tx::bytes [%0], [%1], 1024, [%2];"
                     ::"r"(wb + KC_IN + b * KC_BUF + c * KC_UL), "l"(g_kvT + ch * 256 + c * 64), "r"(bar + 8 * b) : "memory");
    }
  };
  auto fetch_k = [&](int ch) {
#pragma unroll
    for (int r = 0; r < 2; r++) {
      const int m = r * 128 + t128;
      const bf16* src = ssm_k + (size_t)ch * SEQ + m * 8;
      kw[r] = ldg_nc_v4(src);
      pw[r] = (m > 0) ? *reinterpret_cast<const uint32_t*>(src - 2) : 0u;
    }
  };
  auto stash = [&](int b) {
#pragma unroll
    for (int r = 0; r < 2; r++) {
      const uint32_t ka = wb + KC_IN + b * KC_BUF + KC_U + (16 + (r * 128 + t128) * 4) * 4;
      sts_v4(ka, make_uint4(prmt(kw[r].x, pw[r], 0x7610u), prmt(kw[r].y, kw[r].x, 0x7610u), prmt(kw[r].z, kw[r].y, 0x7610u), prmt(kw[r].w, kw[r].z, 0x7610u)));
      sts_v4(ka + 4160, make_uint4(prmt(kw[r].x, 0, 0x1032u), prmt(kw[r].y, 0, 0x1032u), prmt(kw[r].z, 0, 0x1032u), prmt(kw[r].w, 0, 0x1032u)));
    }
  };
  if (ch < ch1) { fetch_u(ch, 0); fetch_k(ch); stash(0); }
  fence_async_smem();
  bar_sync(barid, 128);
  const bool hi = __shfl_sync(0xffffffffu, wq >> 1, 0);
  int i = 0;
#pragma unroll 1
  for (; ch < ch1; i++) {
    const int b = (NB == 2) ? (i & 1) : 0, nb = (NB == 2) ? (b ^ 1) : 0, nxt = ch + step;
    const uint32_t ub = wb + KC_IN + b * KC_BUF;
    const uint32_t D2 = 0x10001u * (uint32_t)__bfloat16_as_ushort(ssm_D[ch]);
    if (nxt < ch1) { if (NB == 2) fetch_u(nxt, nb); fetch_k(nxt); }
    uint32_t dl = ((ub & 0x3FFFF) >> 4) | ((KC_UL >> 4) << 16);
    asm volatile("" : "+r"(dl));
    const uint64_t db = (8ull << 32) | __shfl_sync(0xffffffffu, dl + (lane >> 5), 0);
    const uint32_t ka = ub + KC_U + (g & 1) * 4160 + (((16 * (wq & 1) + g - 2 * tq) >> 1) + 16 + (wq >> 1) * 128) * 4;
    mbar_wait(bar + 8 * b, (NB == 2 ? i >> 1 : i) & 1);
    float acc[32];
    kc_mma<NB == 2>(acc, ka, db, __uint_as_float(lds_u32(ub + KC_U)));
    if (t128 == 0) asm volatile("cp.async.bulk.wait_group.read 0;" ::: "memory");
    {
      const int n = 32 * (wq >> 1) + 8 * (mi >> 1) + r8, c = 2 * (wq & 1) + (mi & 1), a = 63 - n;
      const uint32_t ex = wb + KC_EX + wq * 2048 + lane * 16, ua = ub + c * KC_UL + n * 16, oa = wb + a * 64 + ((c ^ ((a >> 1) & 3)) << 4);
      if (hi) kc_finish<1>(acc, ex, ua, oa, D2, barid); else kc_finish<0>(acc, ex, ua, oa, D2, barid);
    }
    if (nxt < ch1) stash(nb);
    fence_async_smem();
    bar_sync(barid, 128);
    if (NB == 1 && nxt < ch1) fetch_u(nxt, 0);
    if (t128 == 0) {
      asm volatile("cp.async.bulk.tensor.2d.global.shared::cta.bulk_group [%0, {%2, %3}], [%1];" ::"l"(tmY), "r"(wb), "r"(0), "r"(ch * 64) : "memory");
      asm volatile("cp.async.bulk.commit_group;" ::: "memory");
    }
    ch = nxt;
  }
  if (t128 == 0) {
    asm volatile("cp.async.bulk.wait_group 0;\nfence.proxy.async.global;" ::: "memory");
    asm volatile("red.release.gpu.global.add.u32 [%0], %1;" ::"l"(&g_conv_done), "r"(i) : "memory");
  }
}

__global__ void __cluster_dims__(2, 1, 1) __launch_bounds__(512, 1)
kc_conv(const __grid_constant__ CUtensorMap tmY, const bf16* __restrict__ ssm_k, const bf16* __restrict__ ssm_D) {
  extern __shared__ __align__(1024) uint8_t smem[];
  const int wg = __shfl_sync(0xffffffffu, threadIdx.x >> 7, 0);
  conv_wg<2>(smem_u32(smem) + wg * KC_WG, 1 + wg, wg * 4 + blockIdx.x, 16, KC_BG, &tmY, ssm_k, ssm_D);
}

constexpr int KA_ST = 3, KA_SMEM = KA_ST * 65536 + 64;
__global__ void __cluster_dims__(2, 1, 1) __launch_bounds__(512, 1)
ka_prep(const __grid_constant__ CUtensorMap tmK, const __grid_constant__ CUtensorMap tmV, const bf16* __restrict__ q, const bf16* __restrict__ gate_w,
        const bf16* __restrict__ shift_k) {
  extern __shared__ __align__(1024) uint8_t smem[];
  const uint32_t sb = smem_u32(smem), bar = sb + KA_ST * 65536;
  const int tid = threadIdx.x, lane = tid & 31, warp = tid >> 5, g = lane >> 2, tq = lane & 3, mi = lane >> 3, r8 = lane & 7;
  auto issue = [&](int it) {
    const uint32_t dst = sb + (it % KA_ST) * 65536, b = bar + 8 * (it % KA_ST);
    mbar_expect_tx(b, 65536);
#pragma unroll
    for (int i = 0; i < 4; i++)
      asm volatile("cp.async.bulk.tensor.4d.shared::cluster.global.mbarrier::complete_tx::bytes [%0], [%1, {%3, %4, %5, %4}], [%2];"
                   ::"r"(dst + i * 16384), "l"((i & 2) ? &tmV : &tmK), "r"(b), "r"(blockIdx.x * 256 + (it >> 4) * 128 + (i & 1) * 64), "r"(0), "r"((it & 15) * 4) : "memory");
  };
  if (tid == 0) {
    for (int i = 0; i < KA_ST; i++) mbar_init(bar + 8 * i, 1);
    asm volatile("fence.mbarrier_init.release.cluster;" ::: "memory");
    for (int i = 0; i < KA_ST - 1; i++) issue(i);
  }
  uint4 gw[4], xv[4];
#pragma unroll
  for (int i = 0; i < 4; i++) gw[i] = *reinterpret_cast<const uint4*>(gate_w + i * 256 + lane * 8);
  const bf16* qrow = q + (size_t)(blockIdx.x * 512 + warp) * DM + lane * 8;
#pragma unroll
  for (int i = 0; i < 4; i++) xv[i] = ldg_nc_v4(qrow + i * 256);
  const uint32_t la = (warp >> 3) * 16384 + (8 * mi + r8) * 128 + (((warp & 7) ^ r8) << 4);
  uint32_t s0 = 0, s1 = 0, s2 = 0, s3 = 0, h0 = 0, h1 = 0;
  __syncthreads();
#pragma unroll 1
  for (int it = 0; it < 32; it++) {
    const int ch = blockIdx.x * 256 + (it >> 4) * 128 + warp * 8 + g;
    if ((it & 15) == 0) {
      const uint2 t = *reinterpret_cast<const uint2*>(shift_k + ch * 4);
      s0 = prmt(t.x, 0, 0x1010u); s1 = prmt(t.x, 0, 0x3232u); s2 = prmt(t.y, 0, 0x1010u); s3 = prmt(t.y, 0, 0x3232u);
      h0 = h1 = 0;
    }
    if (tid == 0 && it + KA_ST - 1 < 32) issue(it + KA_ST - 1);
    {
      float s = 0.f;
#pragma unroll
      for (int i = 0; i < 4; i++)
#pragma unroll
        for (int c = 0; c < 4; c++) {
          const uint32_t pr = bmul2(reinterpret_cast<const uint32_t*>(&xv[i])[c], reinterpret_cast<const uint32_t*>(&gw[i])[c]);
          s += bf_lo(pr) + bf_hi(pr);
        }
      if (it + 1 < 32) {
#pragma unroll
        for (int i = 0; i < 4; i++) xv[i] = ldg_nc_v4(qrow + (size_t)(it + 1) * 16 * DM + i * 256);
      }
#pragma unroll
      for (int o = 16; o > 0; o >>= 1) s += __shfl_xor_sync(0xffffffffu, s, o);
      if (lane == 0) { const float z = rbf(s); g_gate[blockIdx.x * 512 + it * 16 + warp] = rbf(1.f / (1.f + __expf(-z))); }
    }
    mbar_wait(bar + 8 * (it % KA_ST), (it / KA_ST) & 1);
    const uint32_t src = sb + (it % KA_ST) * 65536 + la;
    uint32_t kk[18], vv[16];
#pragma unroll
    for (int c = 0; c < 4; c++) {
      asm volatile("ldmatrix.sync.aligned.m8n8.x4.trans.shared.b16 {%0,%1,%2,%3}, [%4];" : "=r"(kk[2 + 4 * c]), "=r"(kk[3 + 4 * c]), "=r"(kk[4 + 4 * c]), "=r"(kk[5 + 4 * c]) : "r"(src + c * 4096) : "memory");
      asm volatile("ldmatrix.sync.aligned.m8n8.x4.trans.shared.b16 {%0,%1,%2,%3}, [%4];" : "=r"(vv[4 * c]), "=r"(vv[1 + 4 * c]), "=r"(vv[2 + 4 * c]), "=r"(vv[3 + 4 * c]) : "r"(src + 32768 + c * 4096) : "memory");
    }
    {
      const uint32_t a = __shfl_sync(0xffffffffu, kk[16], (lane & 28) | ((tq + 3) & 3)), b = __shfl_sync(0xffffffffu, kk[17], (lane & 28) | ((tq + 3) & 3));
      kk[0] = tq ? a : h0; kk[1] = tq ? b : h1;
      h0 = a; h1 = b;
    }
    uint4* dst = g_kvT + ch * 256 + 63 - (it & 15) * 4 - tq;
#pragma unroll
    for (int c = 0; c < 4; c++) {
      uint32_t o[4];
#pragma unroll
      for (int i = 0; i < 4; i++) {
        const int x = 2 + 4 * c + i;
        uint32_t a = bmul2(prmt(kk[x - 2], kk[x - 1], 0x5432u), s3);
        a = badd2(a, bmul2(kk[x - 1], s2));
        a = badd2(a, bmul2(prmt(kk[x - 1], kk[x], 0x5432u), s1));
        a = badd2(a, bmul2(kk[x], s0));
        o[i] = bmul2(a, vv[4 * c + i]);
      }
      dst[c * 64] = make_uint4(o[0], o[1], o[2], o[3]);
    }
    __syncthreads();
  }
  __threadfence();
  __syncthreads();
  if (tid == 0) asm volatile("red.release.gpu.global.add.u32 [%0], 1;" ::"l"(&g_ka_done) : "memory");
}

constexpr uint32_t XW_MEM = 0, XW_PROBE = 65536, XW_O = 131072, XW_VX = 262144, XW_VM = 524288, XW_SLOT = 1u << 20;
constexpr uint32_t XW_SX = 2u << 20, XW_SXS = 262144, XW_DRY = 4u << 20;
__device__ uint4 g_xw[(9 << 20) / 16];
__device__ __forceinline__ int nstep_() { int n; asm volatile("mov.u32 %0, %%nctaid.x;" : "=r"(n)); return n >> 1; }
#define NSTEP nstep_()
#define K1_DRY (gridDim.x < 128)
#define CSYNC 1
constexpr int KR = 24;
#define POLL_MAX ((int)(gridDim.x >> 7) * 200000)

constexpr uint32_t Q_WRES = 0, Q_XT = 65536, Q_STG = 98304;
constexpr uint32_t Q_MEMS = 131072, Q_KXEX = Q_MEMS + 8192, Q_QEX = Q_KXEX + 8192, Q_KEX = Q_QEX + 2048, Q_QF = Q_KEX + 2048, Q_KX = Q_QF + 2048,
                   Q_QX = Q_KX + 10240, Q_SMM = Q_QX + 8192, Q_SMX = Q_SMM + 2048, Q_VM = Q_SMX + 1536, Q_TAB = 196608;
static_assert(Q_VM + 1024 <= Q_TAB, "smem");
constexpr uint32_t V_WRES = 0, V_XT = 32768, V_STG = 98304, V_RED = 6144;
constexpr uint32_t V_MEMS = V_STG + 8192, V_VXEX = V_STG + 4 * 16384 + 7168, V_VXS = V_STG + 2 * 16384 + 8192, V_PS = V_STG + 5 * 16384 + 8192,
                   V_TAB = V_STG + 6 * 16384 + 8192, V_PF = V_STG + 16384 + 12288, V_OX = V_STG + 16384 + 8192;
constexpr int OR = 10;
constexpr uint32_t K1_BAR = 229376, K1_SMEM = K1_BAR + 256;
static_assert(K1_SMEM <= 232448, "smem");
constexpr uint32_t MB_X = 0, MB_S = 16, MB_A = 32, MB_B = 64, MB_C = 96, MB_D = 128, MB_P = 160;
enum { B_MEM = 1, B_GOK = 2, B_QF = 3, B_W0 = 4, B_W1 = 5, B_GOX = 6, B_GOQ = 7, B_VM = 8, B_KM = 9, B_SX = 10, B_S = 11, B_PD = 12, B_RED = 2, B_P = 3, B_GOV = 6, B_OX = 7, B_XF = 8 };

__device__ __forceinline__ uint4 ld_rlx(const void* p) {
  uint4 v; asm volatile("ld.relaxed.gpu.global.v4.u32 {%0,%1,%2,%3}, [%4];" : "=r"(v.x), "=r"(v.y), "=r"(v.z), "=r"(v.w) : "l"(p) : "memory"); return v;
}
__device__ __forceinline__ void st_rlx(void* p, uint32_t a, uint32_t b, uint32_t c, uint32_t d) {
  asm volatile("st.relaxed.gpu.global.v4.u32 [%0], {%1,%2,%3,%4};" ::"l"(p), "r"(a), "r"(b), "r"(c), "r"(d) : "memory");
}
__device__ __forceinline__ void st_rlx64(void* p, uint32_t a, uint32_t b) { asm volatile("st.relaxed.gpu.global.v2.u32 [%0], {%1,%2};" ::"l"(p), "r"(a), "r"(b) : "memory"); }
__device__ __forceinline__ void st_rlx32(void* p, uint32_t v) { asm volatile("st.relaxed.gpu.global.u32 [%0], %1;" ::"l"(p), "r"(v) : "memory"); }
__device__ __forceinline__ uint32_t tagw(uint32_t w, uint32_t ph) { return (w & ~1u) | ph; }
__device__ __forceinline__ uint32_t fu(float x) { return __float_as_uint(x); }
__device__ __forceinline__ float uf(uint32_t x) { return __uint_as_float(x); }
__device__ __forceinline__ void mma16816(float (&c)[4], uint32_t a0, uint32_t a1, uint32_t a2, uint32_t a3, uint32_t b0, uint32_t b1) {
  asm volatile("mma.sync.aligned.m16n8k16.row.col.f32.bf16.bf16.f32 {%0,%1,%2,%3}, {%4,%5,%6,%7}, {%8,%9}, {%0,%1,%2,%3};"
               : "+f"(c[0]), "+f"(c[1]), "+f"(c[2]), "+f"(c[3]) : "r"(a0), "r"(a1), "r"(a2), "r"(a3), "r"(b0), "r"(b1));
}
__device__ __forceinline__ void mma16816z(float (&c)[4], uint32_t a0, uint32_t a1, uint32_t a2, uint32_t a3, uint32_t b0, uint32_t b1) {
  asm volatile("mma.sync.aligned.m16n8k16.row.col.f32.bf16.bf16.f32 {%0,%1,%2,%3}, {%4,%5,%6,%7}, {%8,%9}, {%10,%10,%10,%10};"
               : "=f"(c[0]), "=f"(c[1]), "=f"(c[2]), "=f"(c[3]) : "r"(a0), "r"(a1), "r"(a2), "r"(a3), "r"(b0), "r"(b1), "f"(0.f));
}
__device__ __forceinline__ void mma1688(float (&c)[4], uint32_t a0, uint32_t a1, uint32_t b0) {
  asm volatile("mma.sync.aligned.m16n8k8.row.col.f32.bf16.bf16.f32 {%0,%1,%2,%3}, {%4,%5}, {%6}, {%0,%1,%2,%3};"
               : "+f"(c[0]), "+f"(c[1]), "+f"(c[2]), "+f"(c[3]) : "r"(a0), "r"(a1), "r"(b0));
}
__device__ __forceinline__ void ldsm4(uint32_t (&r)[4], uint32_t a) {
  asm volatile("ldmatrix.sync.aligned.m8n8.x4.shared.b16 {%0,%1,%2,%3}, [%4];" : "=r"(r[0]), "=r"(r[1]), "=r"(r[2]), "=r"(r[3]) : "r"(a) : "memory");
}
__device__ __forceinline__ void ldsm4t(uint32_t (&r)[4], uint32_t a) {
  asm volatile("ldmatrix.sync.aligned.m8n8.x4.trans.shared.b16 {%0,%1,%2,%3}, [%4];" : "=r"(r[0]), "=r"(r[1]), "=r"(r[2]), "=r"(r[3]) : "r"(a) : "memory");
}
__device__ __forceinline__ void stsm4t(uint32_t a, uint32_t r0, uint32_t r1, uint32_t r2, uint32_t r3) {
  asm volatile("stmatrix.sync.aligned.m8n8.x4.trans.shared.b16 [%0], {%1,%2,%3,%4};" ::"r"(a), "r"(r0), "r"(r1), "r"(r2), "r"(r3) : "memory");
}
__device__ __forceinline__ uint32_t movm(uint32_t x) { uint32_t y; asm volatile("movmatrix.sync.aligned.m8n8.trans.b16 %0, %1;" : "=r"(y) : "r"(x)); return y; }
__device__ __forceinline__ float2 lds_f2(uint32_t a) { float2 v; asm volatile("ld.shared.v2.f32 {%0,%1}, [%2];" : "=f"(v.x), "=f"(v.y) : "r"(a) : "memory"); return v; }
__device__ __forceinline__ float4 lds_f4(uint32_t a) { float4 v; asm volatile("ld.shared.v4.f32 {%0,%1,%2,%3}, [%4];" : "=f"(v.x), "=f"(v.y), "=f"(v.z), "=f"(v.w) : "r"(a) : "memory"); return v; }
__device__ __forceinline__ void sts_v2(uint32_t a, uint32_t x, uint32_t y) { asm volatile("st.shared.v2.u32 [%0], {%1,%2};" ::"r"(a), "r"(x), "r"(y) : "memory"); }
__device__ __forceinline__ void sts_f4(uint32_t a, float x, float y, float z, float w) { asm volatile("st.shared.v4.f32 [%0], {%1,%2,%3,%4};" ::"r"(a), "f"(x), "f"(y), "f"(z), "f"(w) : "memory"); }
__device__ __forceinline__ void sta_f4(uint32_t a, float x, float y, float z, float w, uint32_t bar) {
  asm volatile("st.async.weak.shared::cluster.mbarrier::complete_tx::bytes.v4.f32 [%0], {%1,%2,%3,%4}, [%5];" ::"r"(a), "f"(x), "f"(y), "f"(z), "f"(w), "r"(bar) : "memory");
}
__device__ __forceinline__ void sta_u4(uint32_t a, uint32_t x, uint32_t y, uint32_t z, uint32_t w, uint32_t bar) {
  asm volatile("st.async.weak.shared::cluster.mbarrier::complete_tx::bytes.v4.b32 [%0], {%1,%2,%3,%4}, [%5];" ::"r"(a), "r"(x), "r"(y), "r"(z), "r"(w), "r"(bar) : "memory");
}
template <int O, int N> __device__ __forceinline__ void send8(uint32_t a, const float (&d)[N], uint32_t bar) {
  sta_u4(a, pack_bf16(d[O], d[O + 1]), pack_bf16(d[O + 2], d[O + 3]), pack_bf16(d[O + 4], d[O + 5]), pack_bf16(d[O + 6], d[O + 7]), bar);
}
template <int O, int N> __device__ __forceinline__ uint4 pack8(const float (&d)[N]) {
  return make_uint4(pack_bf16(d[O], d[O + 1]), pack_bf16(d[O + 2], d[O + 3]), pack_bf16(d[O + 4], d[O + 5]), pack_bf16(d[O + 6], d[O + 7]));
}
template <int O, int N> __device__ __forceinline__ uint4 add8(const float (&d)[N], const uint4& p) {
  return make_uint4(pack_bf16(d[O] + bf_lo(p.x), d[O + 1] + bf_hi(p.x)), pack_bf16(d[O + 2] + bf_lo(p.y), d[O + 3] + bf_hi(p.y)),
                    pack_bf16(d[O + 4] + bf_lo(p.z), d[O + 5] + bf_hi(p.z)), pack_bf16(d[O + 6] + bf_lo(p.w), d[O + 7] + bf_hi(p.w)));
}
__device__ __forceinline__ void stsm4t(uint32_t a, const uint4& r) { stsm4t(a, r.x, r.y, r.z, r.w); }
__device__ __forceinline__ void sta_f2(uint32_t a, float x, float y, uint32_t bar) {
  asm volatile("st.async.weak.shared::cluster.mbarrier::complete_tx::bytes.v2.f32 [%0], {%1,%2}, [%3];" ::"r"(a), "f"(x), "f"(y), "r"(bar) : "memory");
}
__device__ __forceinline__ uint32_t mapa(uint32_t a, uint32_t r) { uint32_t o; asm volatile("mapa.shared::cluster.u32 %0, %1, %2;" : "=r"(o) : "r"(a), "r"(r)); return o; }
__device__ __forceinline__ void mbar_wait1(uint32_t bar, uint32_t parity) {
  asm volatile("{\n.reg .pred p;\n.reg .u32 c;\nmbarrier.try_wait.parity.shared::cta.b64 p, [%0], %1;\n@p bra.uni DONE;\nmov.u32 c, 0;\n"
               "AGAIN:\nmbarrier.try_wait.parity.shared::cta.b64 p, [%0], %1;\n@p bra.uni DONE;\nadd.u32 c, c, 1;\nsetp.lt.u32 p, c, 0x400000;\n@p bra.uni AGAIN;\nDONE:\n}"
               ::"r"(bar), "r"(parity) : "memory");
}
__device__ __forceinline__ void arrive_e(uint32_t bar) {
  asm volatile("{\n.reg .pred p;\nelect.sync _|p, 0xffffffff;\n@p mbarrier.arrive.shared::cta.b64 _, [%0];\n}" ::"r"(bar) : "memory");
}
__device__ __forceinline__ void expect_e(uint32_t bar, uint32_t bytes) {
  asm volatile("{\n.reg .pred p;\nelect.sync _|p, 0xffffffff;\n@p mbarrier.arrive.expect_tx.shared::cta.b64 _, [%0], %1;\n}" ::"r"(bar), "r"(bytes) : "memory");
}
__device__ __forceinline__ float ex2(float x) { float y; asm("ex2.approx.ftz.f32 %0, %1;" : "=f"(y) : "f"(x)); return y; }
__device__ __forceinline__ float rcp(float x) { float y; asm("rcp.approx.ftz.f32 %0, %1;" : "=f"(y) : "f"(x)); return y; }
__device__ __forceinline__ uint32_t phase_of(int n) { return (uint32_t)(((n >> 1) & 1) ^ 1); }
__device__ __forceinline__ uint32_t clk() { uint64_t c; asm volatile("mov.u64 %0, %%clock64;" : "=l"(c)::"memory"); return (uint32_t)c; }
__device__ __forceinline__ void wait_until(uint32_t t) {
  asm volatile("{\n.reg .pred p;\n.reg .u64 c;\n.reg .u32 l, h;\nAGAIN:\nmov.u64 c, %%clock64;\nmov.b64 {l, h}, c;\nsub.u32 l, l, %0;\nsetp.lt.s32 p, l, 0;\n@p bra.uni AGAIN;\n}" ::"r"(t) : "memory");
}
__device__ __forceinline__ void cluster_sync_all() {
  bar_sync(0, 256);
  asm volatile("barrier.cluster.arrive.relaxed.aligned;\nbarrier.cluster.wait.aligned;" ::: "memory");
}
__device__ __forceinline__ uint32_t side_off(uint32_t off, uint32_t c) { return off + (((c ^ __popc((off >> 12) & 0xb2u)) & 1u) << 12); }
#define SCHED() asm volatile("pmevent 1;" ::: "memory")
#define PIN64(x) asm volatile("" : "+l"(x))
#define PIN32(x) asm volatile("" : "+r"(x))

__device__ __forceinline__ uint32_t bad2(uint32_t a, uint32_t b, uint32_t ph) { uint32_t r; asm("lop3.b32 %0, %1, %2, %3, 0x7e;" : "=r"(r) : "r"(a), "r"(b), "r"(ph)); return r; }
__device__ __forceinline__ uint32_t or3(uint32_t a, uint32_t b, uint32_t c) { uint32_t r; asm("lop3.b32 %0, %1, %2, %3, 0xfe;" : "=r"(r) : "r"(a), "r"(b), "r"(c)); return r; }
template <int N> __device__ __forceinline__ bool tags_ok(const uint4 (&v)[N], uint32_t ph) {
  uint32_t bad;
  if constexpr (N == 2) bad = bad2(v[0].x, v[1].x, ph);
  if constexpr (N == 4) bad = or3(bad2(v[0].x, v[1].x, ph), bad2(v[2].x, v[3].x, ph), 0);
  if constexpr (N == 8) bad = or3(bad2(v[0].x, v[1].x, ph), bad2(v[2].x, v[3].x, ph), bad2(v[4].x, v[5].x, ph)), bad = or3(bad, bad2(v[6].x, v[7].x, ph), 0);
  return __all_sync(0xffffffffu, (bad & 1) == 0);
}
__device__ __forceinline__ void reload(uint4& v, const uint8_t* p, uint32_t ph) {
  asm volatile("{\n.reg .pred p;\n.reg .b32 t;\nxor.b32 t, %0, %5;\nand.b32 t, t, 1;\nsetp.ne.u32 p, t, 0;\n@p ld.relaxed.gpu.global.v4.u32 {%0,%1,%2,%3}, [%4];\n}"
               : "+r"(v.x), "+r"(v.y), "+r"(v.z), "+r"(v.w) : "l"(p), "r"(ph) : "memory");
}
__device__ __forceinline__ uint32_t lds_vol(uint32_t a) { uint32_t v; asm volatile("ld.volatile.shared.u32 %0, [%1];" : "=r"(v) : "r"(a) : "memory"); return v; }
#define DLY_UP 64
#define DLY_DN 4
__device__ __forceinline__ uint4 badd4(const uint4& a, const uint4& b) { return make_uint4(badd2(a.x, b.x), badd2(a.y, b.y), badd2(a.z, b.z), badd2(a.w, b.w)); }
template <int N, int ST> __device__ __forceinline__ void repoll(uint4 (&v)[N], const uint8_t* p0, const uint8_t* p1, uint32_t ph, int* dly = nullptr) {
  if (!tags_ok<N>(v, ph)) {
    if (dly) *dly = 1;
#pragma unroll 1
    for (int it = 0; it < POLL_MAX; it++) {
#pragma unroll
      for (int i = 0; i < N; i++) reload(v[i], (i < N / 2) ? p0 + i * ST : p1 + (i - N / 2) * ST, ph);
      if (tags_ok<N>(v, ph)) break;
    }
  }
#pragma unroll
  for (int i = 0; i < N; i++) asm volatile("" : "+r"(v[i].x), "+r"(v[i].y), "+r"(v[i].z), "+r"(v[i].w));
}
template <int N, int ST> __device__ __forceinline__ void poll(uint4 (&v)[N], const uint8_t* p0, const uint8_t* p1, uint32_t ph, int* dly = nullptr) {
#pragma unroll
  for (int i = 0; i < N; i++) v[i] = ld_rlx((i < N / 2) ? p0 + i * ST : p1 + (i - N / 2) * ST);
  repoll<N, ST>(v, p0, p1, ph, dly);
}
__device__ __forceinline__ uint4 tab(uint32_t tb, int k) {
  uint4 v; asm volatile("ld.volatile.shared.v4.u32 {%0,%1,%2,%3}, [%4];" : "=r"(v.x), "=r"(v.y), "=r"(v.z), "=r"(v.w) : "r"(tb + k * 4096) : "memory"); return v;
}
__device__ __forceinline__ uint32_t opaque(uint32_t slot, uint32_t v) { sts_u32(slot, v); return lds_vol(slot); }
__device__ __forceinline__ uint4 tabo(uint32_t a) { return tab(a, 0); }
__device__ __forceinline__ void quad_store(uint8_t* dst, const uint32_t (&ox)[4], int tq) {
  uint32_t a0 = ox[0], a1 = ox[1], a2 = ox[2], a3 = ox[3];
  const bool b0 = tq & 1, b1 = tq & 2;
  uint32_t s0 = b0 ? a0 : a1, s1 = b0 ? a2 : a3;
  s0 = __shfl_xor_sync(0xffffffffu, s0, 1); s1 = __shfl_xor_sync(0xffffffffu, s1, 1);
  if (b0) { a0 = s0; a2 = s1; } else { a1 = s0; a3 = s1; }
  uint32_t u0 = b1 ? a0 : a2, u1 = b1 ? a1 : a3;
  u0 = __shfl_xor_sync(0xffffffffu, u0, 2); u1 = __shfl_xor_sync(0xffffffffu, u1, 2);
  if (b1) { a0 = u0; a1 = u1; } else { a2 = u0; a3 = u1; }
  *reinterpret_cast<uint4*>(dst) = make_uint4(a0, a1, a2, a3);
}
__device__ __forceinline__ uint8_t* mkptr(uint32_t lo, uint32_t hi) { return reinterpret_cast<uint8_t*>(((uint64_t)hi << 32) | lo); }
__device__ __forceinline__ uint32_t plo(const void* p) { return (uint32_t)reinterpret_cast<uint64_t>(p); }
__device__ __forceinline__ uint32_t phi(const void* p) { return (uint32_t)(reinterpret_cast<uint64_t>(p) >> 32); }

#define TS(i) do { } while (0)
#define TSW(i, W) do { } while (0)
#define TSG(i) do { } while (0)
#define TSA(i) do { } while (0)
#define TS_DUMP() do { } while (0)
#define KBAR 0
#define SACC 2
#define VMP 0
#define TAILSKIP 1
#define SPEC 0
#define KORD 0
#define PROBE_N 3
#define EXP 4
#define XSKIP 0
#define XSKIP_LO 0
#define XSKIP_X 0
#define NOATT 0
#define XPOS 0
#define DLY_Q 1700
#define DLY_V 250
#define DLY_O 1700

#define KP1 5
#define KP2 10
#define KP3 15
#define GOI 0
template <int H> __device__ __forceinline__ void proj2_pre(uint32_t (&at)[8][4], uint32_t wres) {
#pragma unroll
  for (int m = 0; m < 4; m++) ldsm4t(at[4 * H + m], wres + (2 * H + (m >> 1)) * 2048 + (m & 1) * 16384);
}
template <int GO> __device__ constexpr int p2_p(int n) { return GO ? (n == 0 ? 0 : n == 1 ? 1 : n == 2 ? 9 : 14) : (n == 0 ? 0 : n == 1 ? KP1 : n == 2 ? KP2 : KP3); }
template <int GO> __device__ constexpr int p2_s(int i) { return i == p2_p<GO>(0) ? 0 : i == p2_p<GO>(1) ? 1 : i == p2_p<GO>(2) ? 2 : i == p2_p<GO>(3) ? 3 : -1; }
template <int GO> __device__ constexpr int p2_r(int i) { return i - 1 - (i > p2_p<GO>(1)) - (i > p2_p<GO>(2)) - (i > p2_p<GO>(3)); }
template <int GO> __device__ constexpr int p2_pair(int i) { return p2_s<GO>(i) >= 0 ? 12 + p2_s<GO>(i) : p2_r<GO>(i); }
template <int GO> __device__ __forceinline__ void proj2(float (&d)[8], const uint32_t (&wf)[2][KR][4], uint32_t (&at)[8][4], uint32_t wres, uint32_t mems) {
  float acc[2][2][4];
  uint32_t b[2][4];
  ldsm4(b[0], mems + p2_pair<GO>(0) * 512);
#pragma unroll
  for (int i = 0; i < 16; i++) {
    if (i + 1 < 16) ldsm4(b[(i + 1) & 1], mems + p2_pair<GO>(i + 1) * 512);
    if (GO || KP1 == 1) {
      if (i >= 2 && i < 6) ldsm4t(at[i - 2], wres + (4 + ((i - 2) >> 1)) * 2048 + ((i - 2) & 1) * 16384);
      if (i >= 7 && i < 12 && i != 9) { const int m = i - 7 - (i > 9); ldsm4t(at[4 + m], wres + (6 + (m >> 1)) * 2048 + (m & 1) * 16384); }
    } else {
#pragma unroll
      for (int n = 1; n < 4; n++) {
        const int m = i - (p2_p<GO>(n) - 5);
        if (m >= 0 && m < 4) ldsm4t(at[(n & 1) * 4 + m], wres + (2 * n + (m >> 1)) * 2048 + (m & 1) * 16384);
      }
    }
    const uint32_t (&bb)[4] = b[i & 1];
    if (GOI > 0 && i == GOI && GO) bar_arrive(GO, 256);
#pragma unroll
    for (int u = 0; u < 2; u++)
#pragma unroll
      for (int t = 0; t < 2; t++) {
        const uint32_t* a = (p2_s<GO>(i) < 0) ? wf[t][p2_s<GO>(i) < 0 ? 2 * p2_r<GO>(i) + u : 0] : at[(p2_s<GO>(i) & 1) * 4 + 2 * u + t];
        if (i == 0) mma16816z(acc[t][u], a[0], a[1], a[2], a[3], bb[2 * u], bb[2 * u + 1]);
        else mma16816(acc[t][u], a[0], a[1], a[2], a[3], bb[2 * u], bb[2 * u + 1]);
      }
  }
#pragma unroll
  for (int t = 0; t < 2; t++)
#pragma unroll
    for (int e = 0; e < 4; e++) d[4 * t + e] = acc[t][0][e] + acc[t][1][e];
}
constexpr uint32_t SMEM0 = 0x400;
__device__ constexpr uint64_t cdesc(uint32_t off) { return (0x40000040ull << 32) | 0x10000u | ((SMEM0 + off) >> 4); }
template <uint32_t AOFF, uint32_t XOFF, int K0 = 0, int K1 = 32, bool IL = true> __device__ __forceinline__ void xproj(float (&ax)[16], const uint32_t (&wf)[KR][4]) {
#pragma unroll
  for (int i = K0; i < (XSKIP && AOFF >= XSKIP_LO && XOFF >= XSKIP_X ? (K0 == 0 ? 1 : K0) : K1); i++) {
    const int ks = !IL ? i : ((i & 3) == 3) ? KR + (i >> 2) : 3 * (i >> 2) + (i & 3);
    if (ks < KR) wg_rs_n32<0>(ax, wf[ks < KR ? ks : 0][0], wf[ks < KR ? ks : 0][1], wf[ks < KR ? ks : 0][2], wf[ks < KR ? ks : 0][3], cdesc(XOFF) + (ks >> 2) * 256 + (ks & 3) * 2, i != 0);
    else if (EXP == 3) wg_rs_n32<0>(ax, wf[0][0], wf[0][1], wf[0][2], wf[0][3], cdesc(XOFF) + (ks >> 2) * 256 + (ks & 3) * 2, 1);
    else wg_ss_n32_ta<0>(ax, cdesc(AOFF) + (ks - KR) * 128, cdesc(XOFF) + (ks >> 2) * 256 + (ks & 3) * 2, 1);
  }
  wg_commit();
}
__device__ __forceinline__ void wg_ss_n40(float (&d)[20], uint64_t da, uint64_t db, int sd) {
  asm volatile("{\n.reg .pred p;\nsetp.ne.b32 p, %22, 0;\n"
    "wgmma.mma_async.sync.aligned.m64n40k16.f32.bf16.bf16 {%0, %1, %2, %3, %4, %5, %6, %7, %8, %9, %10, %11, %12, %13, %14, %15, %16, %17, %18, %19}, %20, %21, p, 1, 1, 0, 0;\n}\n"
    : "+f"(d[0]), "+f"(d[1]), "+f"(d[2]), "+f"(d[3]), "+f"(d[4]), "+f"(d[5]), "+f"(d[6]), "+f"(d[7]), "+f"(d[8]), "+f"(d[9]), "+f"(d[10]), "+f"(d[11]), "+f"(d[12]), "+f"(d[13]),
      "+f"(d[14]), "+f"(d[15]), "+f"(d[16]), "+f"(d[17]), "+f"(d[18]), "+f"(d[19]) : "l"(da), "l"(db), "r"(sd));
}
__device__ constexpr uint64_t cdesc0(uint32_t off, uint32_t lbo) { return (8ull << 32) | ((uint64_t)(lbo >> 4) << 16) | ((SMEM0 + off) >> 4); }
template <int P> __device__ __forceinline__ void q_shadow(const uint32_t (&wf)[2][KR][4], uint32_t dst, uint32_t (&at)[8][4], uint32_t wres) {
  float ax[2][16];
  wg_fence();
  xproj<Q_WRES, Q_XT + P * 32768>(ax[0], wf[0]);
  xproj<Q_WRES + 16384, Q_XT + P * 32768, 0, 10>(ax[1], wf[1]);
  wg_wait<1>(); fence_regs(ax[0]);
  stsm4t(dst, pack_bf16(ax[0][0], ax[0][1]), pack_bf16(ax[0][2], ax[0][3]), pack_bf16(ax[0][4], ax[0][5]), pack_bf16(ax[0][6], ax[0][7]));
  stsm4t(dst + 256, pack_bf16(ax[0][8], ax[0][9]), pack_bf16(ax[0][10], ax[0][11]), pack_bf16(ax[0][12], ax[0][13]), pack_bf16(ax[0][14], ax[0][15]));
  if (EXP != 4) { proj2_pre<0>(at, wres); proj2_pre<1>(at, wres); }
  xproj<Q_WRES + 16384, Q_XT + P * 32768, 10, 32>(ax[1], wf[1]);
  asm volatile("cp.async.wait_all;" ::: "memory");
  wg_wait<0>(); fence_regs(ax[1]);
  if (EXP == 4) { proj2_pre<0>(at, wres); proj2_pre<1>(at, wres); }
  stsm4t(dst + 4096, pack_bf16(ax[1][0], ax[1][1]), pack_bf16(ax[1][2], ax[1][3]), pack_bf16(ax[1][4], ax[1][5]), pack_bf16(ax[1][6], ax[1][7]));
  stsm4t(dst + 4096 + 256, pack_bf16(ax[1][8], ax[1][9]), pack_bf16(ax[1][10], ax[1][11]), pack_bf16(ax[1][12], ax[1][13]), pack_bf16(ax[1][14], ax[1][15]));
}
#define NW 0
#define NW1 0
template <int P, class F1, class F> __device__ __forceinline__ void k_shadow(const uint32_t (&wf)[2][KR][4], const uint4& t5, const uint32_t& bar, uint32_t tb, uint4& t0,
                                                                             uint4 (&kx)[2], uint32_t& tgo, F1&& mid1, F&& mid) {
  float ax[2][16];
  wg_fence();
  if (NW1 > 0) xproj<Q_WRES + 32768, Q_XT + P * 32768, 0, NW1, false>(ax[0], wf[0]);
  mid1();
  wg_fence();
  if (NW > 0) xproj<Q_WRES + 32768, Q_XT + P * 32768, NW1, NW1 + NW, false>(ax[0], wf[0]);
  mid();
  wg_fence();
  xproj<Q_WRES + 32768, Q_XT + P * 32768, NW1 + NW, 32, NW1 + NW == 0>(ax[0], wf[0]);
  xproj<Q_WRES + 49152, Q_XT + P * 32768, 0, 10>(ax[1], wf[1]);
  wg_wait<1>(); fence_regs(ax[0]);
  const uint4 k0 = pack8<0>(ax[0]), k1 = pack8<8>(ax[0]);
  sta_u4(t5.x, k0.x, k0.y, k0.z, k0.w, t5.y); sta_u4(t5.x + 512, k1.x, k1.y, k1.z, k1.w, t5.y);
  xproj<Q_WRES + 49152, Q_XT + P * 32768, 10, 25>(ax[1], wf[1]);
  xproj<Q_WRES + 49152, Q_XT + P * 32768, 25, 32>(ax[1], wf[1]);
  t0 = tab(tb, 0);
  tgo = lds_vol(tb + 16384 + 4);
  bar_sync(B_SX, 256);
  wg_wait<1>();
  bar_arrive(B_GOQ, 256);
  mbar_wait1(bar, P);
  const uint4 a0 = lds_v4(t5.z), b0 = lds_v4(t5.z + 512);
  wg_wait<0>(); fence_regs(ax[1]);
  const uint4 k2 = pack8<0>(ax[1]), k3 = pack8<8>(ax[1]);
  sta_u4(t5.x + 1024, k2.x, k2.y, k2.z, k2.w, t5.y + 32); sta_u4(t5.x + 1536, k3.x, k3.y, k3.z, k3.w, t5.y + 32);
  stsm4t(t5.w, badd4(k0, a0)); stsm4t(t5.w + 256, badd4(k1, b0));
  mbar_wait1(bar + 32, P);
  kx[0] = badd4(k2, lds_v4(t5.z + 1024)); kx[1] = badd4(k3, lds_v4(t5.z + 1536));
}
template <int P, class F> __device__ __forceinline__ void v1_shadow(const uint32_t (&vf)[KR][4], const uint32_t& rex, const uint32_t& rb, F&& mid) {
  float ax[16];
  wg_fence();
  xproj<V_WRES + 16384, V_XT + P * 32768, 0, 25>(ax, vf);
  xproj<V_WRES + 16384, V_XT + P * 32768, 25, 32>(ax, vf);
  mid();
  wg_wait<1>();
  bar_arrive(B_GOV, 256);
  wg_wait<0>(); fence_regs(ax);
  send8<0>(rex, ax, rb); send8<8>(rex + 512, ax, rb);
}
template <int P> __device__ __forceinline__ void v0_shadow(const uint32_t (&vf)[KR][4], uint32_t ex, uint32_t bar, uint8_t* xp, uint32_t vs, uint32_t pn) {
  float ax[16];
  wg_fence();
  xproj<V_WRES, V_XT + P * 32768>(ax, vf);
  mbar_wait1(bar, P);
  const uint4 a = lds_v4(ex), b = lds_v4(ex + 512);
  wg_wait<0>(); fence_regs(ax);
  const uint4 c = add8<0>(ax, a), d = add8<8>(ax, b);
  st_rlx(xp, tagw(c.x, pn), c.z, d.x, d.z); st_rlx(xp + 512, tagw(c.y, pn), c.w, d.y, d.w);
  sts_v4(vs, make_uint4(c.x, c.z, d.x, d.z)); sts_v4(vs + 512, make_uint4(c.y, c.w, d.y, d.w));
}
__device__ __forceinline__ void load_x(uint32_t sb, uint32_t xt, const CUtensorMap* tmX, int n, int j) {
  const uint32_t bar = sb + K1_BAR + MB_X + 8 * (n & 1);
  asm volatile("{\n.reg .pred p;\nelect.sync _|p, 0xffffffff;\n@p mbarrier.arrive.expect_tx.shared::cta.b64 _, [%2], 32768;\n"
               "@p cp.async.bulk.tensor.3d.shared::cluster.global.mbarrier::complete_tx::bytes [%0], [%1, {%3, %4, %5}], [%2];\n}"
               ::"r"(sb + xt + (n & 1) * 32768), "l"(tmX), "r"(bar), "r"(0), "r"(n * SEG), "r"(j * 8) : "memory");
}
__device__ __forceinline__ uint32_t probe_rtt(uint8_t* xw, uint32_t slot, uint32_t c) {
  uint8_t* p = xw + side_off(XW_PROBE, c) + blockIdx.x * 32;
  st_rlx(p, 0, 0, 0, 0); st_rlx(p + 16, 0, 0, 0, 0);
  uint32_t best = 1u << 30;
#pragma unroll 1
  for (int r = 0; r < PROBE_N; r++) {
    const uint32_t t0 = clk();
    uint32_t v; asm volatile("atom.relaxed.gpu.global.add.u32 %0, [%1], 1;" : "=r"(v) : "l"(p) : "memory");
    asm volatile("st.volatile.shared.u32 [%0], %1;" ::"r"(slot), "r"(v) : "memory");
    best = min(best, clk() - t0);
  }
  return best;
}
__device__ __forceinline__ uint32_t my_side(uint32_t bar) { return lds_u32(bar + 244) < lds_u32(bar + 240); }

constexpr float SM_SAFE = 24.f;
constexpr float SL2E = 0.08838834764831845f * 1.4426950408889634f;

template <int WG> __device__ __forceinline__ void qk_load_weights(uint32_t (&wf)[2][KR][4], uint32_t sb, const CUtensorMap* tm) {
  const int tid = threadIdx.x, lane = tid & 31, w = (tid >> 5) & 3, mi = lane >> 3, kr = (mi >> 1) * 8 + (lane & 7), h = blockIdx.x >> 2, j = blockIdx.x & 1;
  const uint32_t lo = kr * 128 + (((2 * w + (mi & 1)) ^ (kr & 7)) << 4), pb = sb + K1_BAR + MB_P + WG * 32, stg = sb + Q_STG + WG * 65536;
#pragma unroll
  for (int i = 0; i < 2 * KR; i++) asm volatile("" : "=r"(wf[i & 1][i >> 1][0]), "=r"(wf[i & 1][i >> 1][1]), "=r"(wf[i & 1][i >> 1][2]), "=r"(wf[i & 1][i >> 1][3]));
  if (!K1_DRY) {
#pragma unroll
  for (int c = 0; c < 3; c++) {
    mbar_wait1(pb + 8 * c, 0);
#pragma unroll
    for (int t = 0; t < 2; t++)
#pragma unroll
      for (int ks = 0; ks < 8; ks++) ldsm4t(wf[t][8 * c + ks], stg + (2 * (c & 1) + t) * 16384 + ks * 2048 + lo);
    if (c == 0) {
      bar_sync(B_W0 + WG, 128);
      if ((tid & 127) == 0) {
        mbar_expect_tx(pb + 16, 32768);
        for (int t = 0; t < 2; t++) tma_load_2d(stg + t * 16384, tm, h * DH + 64 * t, j * 512 + 256, pb + 16);
      }
      __syncwarp();
    }
  }
  mbar_wait1(pb + 24, 0);
  }
  TSG(2);
  cluster_sync_all();
}

__device__ __forceinline__ void role_q(uint32_t sb, const CUtensorMap* tmX, const CUtensorMap* tmW, uint8_t* __restrict__ xw) {
  uint32_t wf[2][KR][4];
  qk_load_weights<0>(wf, sb, tmW);
  const uint32_t tb0 = sb + Q_TAB + threadIdx.x * 16;
  {
    const uint32_t tb = tb0;
    const int h = blockIdx.x >> 2, j = blockIdx.x & 1, lane = threadIdx.x & 31, w = threadIdx.x >> 5, mi = lane >> 3, r8 = lane & 7, kr = (mi >> 1) * 8 + r8;
    const uint32_t BAR = sb + K1_BAR, l16 = sb + lane * 16, qex = l16 + Q_QEX + w * 512, bq = BAR + MB_A + 8 * w;
    const uint8_t* vxp = xw + XW_VX + (2 * h + j) * 4096 + w * 1024 + lane * 16;
    const uint8_t* op = xw + XW_O + (h >> 1) * 8192 + (4 * (h & 1) + 2 * j + (w >> 1)) * 512 + (lane >> 2) * 64 + (w & 1) * 32 + (lane & 3) * 8;
    sts_v4(tb, make_uint4(sb + Q_WRES + kr * 128 + (((2 * w + (mi & 1)) ^ (kr & 7)) << 4), l16, mapa(qex, j ^ 1), mapa(bq, j ^ 1)));
    sts_v4(tb + 4096, make_uint4(plo(vxp), phi(vxp), sb + Q_KX + mi * 640 + (8 * w + r8) * 16, bq));
    sts_v4(tb + 8192, make_uint4(qex, sb + Q_QF + (8 * (mi >> 1) + 2 * w + (mi & 1)) * 128 + r8 * 16, sb + Q_QF + (2 * (mi & 1) + (mi >> 1)) * 128 + r8 * 16, l16 + Q_SMX + (w & 1) * 8 + (w >> 1) * 4));
    sts_v4(tb + 12288, make_uint4(plo(op), plo(xw + side_off(XW_VM + (2 * h + j) * 8192, my_side(BAR)) + w * 512 + lane * 16), l16 + Q_SMM, l16 + Q_SMX + 512 + (w >> 1) * 512 + (w & 1) * 8));
    sts_v4(tb + 16384, make_uint4(BAR, (lane & 1) ? 0u : 1u, l16 + Q_SMX, sb + Q_QX + (2 * w + (mi & 1)) * 512 + (8 * (mi >> 1) + r8) * 16));
  }
  const uint32_t tb = opaque(tb0 + 20480, tb0);
  TSG(6);
  bar_arrive(B_SX, 256);
  uint4 n0, nv;
  uint32_t nq;
  auto prep = [&](int s) {
    n0 = tab(tb, 0); nv = tab(tb, 1); nq = lds_vol(tb + 16384 + 12);
    if (s < NSTEP) mbar_wait1(sb + K1_BAR + MB_X + 8 * (s & 1), (s >> 1) & 1);
    expect_e(nv.w, 512);
    if (s + 1 < NSTEP && __any_sync(0xffffffffu, nv.w == sb + K1_BAR + MB_A + 16)) load_x(sb, Q_XT, tmX, s + 1, blockIdx.x & 1);
  };
  prep(0);
#pragma unroll 1
  for (int s = 0; s < NSTEP; s++) {
    {
      uint4 qh;
      {
        float q[8];
        const uint4 t0 = n0;
        {
          const uint8_t* vxp = mkptr(nv.x ^ ((s & 1) << 20), nv.y);
          cp_async16(tb + 20480, vxp); cp_async16(tb + 24576, vxp + 512);
        }
        bar_sync(B_GOQ, 256);
        TS(6);
        uint32_t at[8][4];
        if (s & 1) q_shadow<1>(wf, nq, at, t0.x); else q_shadow<0>(wf, nq, at, t0.x);
        TS(7);
        bar_sync(B_MEM, 256);
        proj2<B_GOK>(q, wf, at, t0.x, t0.y + Q_MEMS);
        qh = pack8<0>(q);
        sta_u4(t0.z, qh.x, qh.y, qh.z, qh.w, t0.w);
        if (NW1 > 0) bar_arrive(B_PD, 256);
      }
      SCHED();
      TS(1);
      const uint32_t ph = phase_of(s), par = s & 1;
      const uint4 t1 = tab(tb, 1), t2 = tab(tb, 2), t3 = tab(tb, 3), t4 = tab(tb, 4);
      uint32_t kx[4][4];
#pragma unroll
      for (int i = 0; i < 4; i++) ldsm4(kx[i], t1.z + i * 2560);
      uint8_t* op = mkptr(t3.x ^ (par << 20), t1.y);
      const uint32_t tbit = t4.y & ph, smx = t3.w;
      SCHED();
      mbar_wait1(t1.w, par);
      const uint4 qp = lds_v4(t2.x);
      const uint8_t* vp = mkptr(t3.y ^ (par << 20), t1.y);
      uint4 vm[2];
      if (VMP == 0) { vm[0] = ld_rlx(vp); vm[1] = ld_rlx(vp + 2048); }
      stsm4t(t2.y, badd4(qh, qp));
      bar_arrive(B_QF, 256);
      bar_sync(B_W1, 128);
      if (VMP == 1) { vm[0] = ld_rlx(vp); vm[1] = ld_rlx(vp + 2048); }
      {
        float c[4][4];
        uint32_t a[4][4];
#pragma unroll
        for (int i = 0; i < 4; i++) ldsm4(a[i], t2.z + i * 512);
#pragma unroll
        for (int i = 0; i < 4; i++) {
          if (i < SACC / 2) { mma16816z(c[2 * i], a[i][0], a[i][1], a[i][2], a[i][3], kx[i][0], kx[i][1]); mma16816z(c[2 * i + 1], a[i][0], a[i][1], a[i][2], a[i][3], kx[i][2], kx[i][3]); }
          else { mma16816(c[(2 * i) % SACC], a[i][0], a[i][1], a[i][2], a[i][3], kx[i][0], kx[i][1]); mma16816(c[(2 * i + 1) % SACC], a[i][0], a[i][1], a[i][2], a[i][3], kx[i][2], kx[i][3]); }
        }
        const float x0 = (SACC == 2 ? c[0][0] + c[1][2] : (c[0][0] + c[1][2]) + (c[2][0] + c[3][2])) * SL2E, x1 = (SACC == 2 ? c[0][1] + c[1][3] : (c[0][1] + c[1][3]) + (c[2][1] + c[3][3])) * SL2E;
        sts_u32(t2.w, pack_bf16(ex2(x0), ex2(x1)) | ((fmaxf(fabsf(x0), fabsf(x1)) <= SM_SAFE) ? 0u : 0x80000000u));
        sts_v2(smx, fu(x0), fu(x1));
      }
      TS(2);
      uint4 vx[2] = {tab(tb, 5), tab(tb, 6)};
      bar_sync(B_S, 256);
      const uint4 p = lds_v4(t4.z);
      const float4 r0 = lds_f4(t3.z), r1 = lds_f4(t3.z + 512);
      {
        uint32_t o0, o1;
        auto pv = [&](const uint4& p, uint32_t pm) {
          float acc[3][4], u0[4], u1[4];
          mma16816z(acc[2], p.x, p.y, p.z, p.w, 0x3F803F80u, 0x3F803F80u);
          mma16816z(acc[0], p.x, p.y, p.z, p.w, vx[0].x, vx[0].y);
          mma16816z(acc[1], p.x, p.y, p.z, p.w, vx[1].x, vx[1].y);
          mma16816z(u0, p.x, p.y, p.z, p.w, vx[0].z, vx[0].w);
          mma16816z(u1, p.x, p.y, p.z, p.w, vx[1].z, vx[1].w);
          mma1688(acc[2], pm, 0u, 0x3F803F80u);
          mma1688(acc[0], pm, 0u, pack_bf16(uf(vm[0].x) + uf(vm[1].x), uf(vm[0].y) + uf(vm[1].y)));
          mma1688(acc[1], pm, 0u, pack_bf16(uf(vm[0].z) + uf(vm[1].z), uf(vm[0].w) + uf(vm[1].w)));
          const float inv = rcp(acc[2][0] + acc[2][2]);
          o0 = (pack_bf16((acc[0][0] + u0[2]) * inv, (acc[0][1] + u0[3]) * inv) & ~t4.y) | tbit; o1 = pack_bf16((acc[1][0] + u1[2]) * inv, (acc[1][1] + u1[3]) * inv);
        };
        const float m0 = (r0.x + r0.z) + (r1.x + r1.z), m1 = (r0.y + r0.w) + (r1.y + r1.w);
        const uint32_t wide = or3(or3(p.x, p.y, p.z), p.w, (fmaxf(fabsf(m0), fabsf(m1)) <= SM_SAFE) ? 0u : 0x80000000u);
        const bool fast = __all_sync(0xffffffffu, (int)or3(wide, or3(bad2(vx[0].x, vx[1].x, ph), bad2(vm[0].x, vm[1].x, ph), 0) << 31, 0) >= 0);
        uint32_t pm = pack_bf16(ex2(m0), ex2(m1));
        pv(p, pm);
        if (fast) { st_rlx64(op, o0, o1); st_rlx64(op + 4096, o0, o1); }
        else {
          repoll<2, 512>(vm, vp, vp + 2048, ph);
          const uint8_t* vxp = mkptr(lds_vol(tb + 4096) ^ (par << 20), lds_vol(tb + 4096 + 4));
          repoll<2, 512>(vx, vxp, vxp + 512, ph);
          uint4 p2 = p;
          if (__any_sync(0xffffffffu, (int)wide < 0)) {
            const float4 sa = lds_f4(t4.z + 512), sb2 = lds_f4(t4.z + 1024);
            float mx = fmaxf(fmaxf(fmaxf(fmaxf(sa.x, sa.y), fmaxf(sa.z, sa.w)), fmaxf(fmaxf(sb2.x, sb2.y), fmaxf(sb2.z, sb2.w))), fmaxf(m0, m1));
            mx = fmaxf(mx, __shfl_xor_sync(0xffffffffu, mx, 1));
            mx = fmaxf(mx, __shfl_xor_sync(0xffffffffu, mx, 2));
            p2 = make_uint4(pack_bf16(ex2(sa.x - mx), ex2(sa.y - mx)), pack_bf16(ex2(sb2.x - mx), ex2(sb2.y - mx)), pack_bf16(ex2(sa.z - mx), ex2(sa.w - mx)),
                            pack_bf16(ex2(sb2.z - mx), ex2(sb2.w - mx)));
            pm = pack_bf16(ex2(m0 - mx), ex2(m1 - mx));
          }
          pv(p2, pm);
          st_rlx64(op, o0, o1); st_rlx64(op + 4096, o0, o1);
        }
      }
      bar_arrive(B_GOX, 256);
      SCHED();
      TS(5);
      TSA(12 + (threadIdx.x >> 5));
      {
        float c[20];
        prep(s + 1);
        const int wu = __shfl_sync(0xffffffffu, (nv.w >> 3) & 3, 0);
        fence_async_smem();
        bar_sync(B_KM, 256);
        wg_fence();
#pragma unroll
        for (int ks = 0; ks < (EXP == 1 ? 1 : 8); ks++) wg_ss_n40(c, cdesc0(Q_QX + ks * 1024, 512), cdesc0(Q_KX + ks * 1280, 640), ks != 0);
        wg_commit();
        uint4* sxp = reinterpret_cast<uint4*>(xw + (XW_SX + par * XW_SXS + ((blockIdx.x >> 2) * 2 + (blockIdx.x & 1)) * 4096 + (threadIdx.x & 31) * 16));
        wg_wait<0>(); fence_regs(c);
        bar_arrive(B_SX, 256);
        if (wu < 2) {
          sxp += wu * 64;
          st_rlx(sxp, tagw(fu(c[0]), ph), fu(c[1]), fu(c[4]), fu(c[5]));
          st_rlx(sxp + 32, tagw(fu(c[2]), ph), fu(c[3]), fu(c[6]), fu(c[7]));
          st_rlx(sxp + 192 - wu * 32, tagw(fu(c[16]), ph), fu(c[17]), fu(c[18]), fu(c[19]));
          if (wu == 1) {
            st_rlx(sxp + 64, tagw(fu(c[8]), ph), fu(c[9]), fu(c[12]), fu(c[13]));
            st_rlx(sxp + 96, tagw(fu(c[10]), ph), fu(c[11]), fu(c[14]), fu(c[15]));
          }
        }
      }
    }
  }
}

__device__ __forceinline__ void role_k(uint32_t sb, const CUtensorMap* tmW, uint8_t* __restrict__ xw, const bf16* __restrict__ mem0) {
  uint32_t wf[2][KR][4];
  qk_load_weights<1>(wf, sb, tmW);
  const uint32_t tb0 = sb + Q_TAB + threadIdx.x * 16;
  {
    const uint32_t tb = tb0;
    const int h = blockIdx.x >> 2, j = blockIdx.x & 1, lane = threadIdx.x & 31, w = (threadIdx.x >> 5) & 3, mi = lane >> 3, r8 = lane & 7, kr = (mi >> 1) * 8 + r8;
    const uint32_t BAR = sb + K1_BAR, l16 = sb + lane * 16, side = my_side(BAR);
    const uint8_t* p0 = xw + (w & 1) * 2048 + lane * 16 + side_off(XW_MEM + (j * 4 + (w >> 1)) * 8192, side);
    const uint32_t smm = sb + Q_SMM + (w >> 1) * 512 + lane * 16 + (w & 1) * 8, kex = l16 + Q_KEX + w * 512, ex = l16 + Q_KXEX + w * 2048;
    sts_v4(tb, make_uint4(sb + Q_WRES + 32768 + kr * 128 + (((2 * w + (mi & 1)) ^ (kr & 7)) << 4), l16 + Q_MEMS + w * 2048, plo(p0), phi(p0)));
    sts_v4(tb + 4096, make_uint4(kex, BAR + MB_B + 8 * w, smm, sb + Q_QF + (8 * (mi & 1) + 2 * w + (mi >> 1)) * 128 + r8 * 16));
    sts_v4(tb + 12288, make_uint4(mapa(kex, j ^ 1), mapa(BAR + MB_B + 8 * w, j ^ 1), l16 + Q_MEMS, sb + Q_KX + (8 * (mi >> 1) + 2 * w + (mi & 1)) * 640 + (32 + r8) * 16));
    sts_v4(tb + 20480, make_uint4(mapa(ex, j ^ 1), mapa(BAR + MB_C + 8 * w, j ^ 1), ex, sb + Q_KX + (2 * w + (mi & 1)) * 640 + (8 * (mi >> 1) + r8) * 16));
#pragma unroll
    for (int i = 0; i < 4; i++) sts_v4(l16 + Q_MEMS + w * 2048 + i * 512, ldg_nc_v4(mem0 + r8 * DM + j * 512 + (16 * w + 4 * i + mi) * 8));
  }
  const uint32_t tb = opaque(sb + Q_SMX + (threadIdx.x & 127) * 4, tb0);
  sts_u32(tb + 16384, DLY_Q);
  uint4 kh = {};
  auto scores = [&](int s) {
    const uint4 t1 = tab(tb, 1);
    const uint32_t kmd = lds_vol(tb + 12288 + 12);
    mbar_wait1(t1.y, s & 1);
    const uint4 kf = badd4(kh, lds_v4(t1.x));
    const uint32_t b0 = movm(kf.x), b1 = movm(kf.y), b2 = movm(kf.z), b3 = movm(kf.w);
    bar_sync(B_QF, 256);
    uint32_t a[4];
    ldsm4(a, t1.w);
    float c0[4], c1[4];
    mma16816z(c0, a[0], a[1], a[2], a[3], b0, b1);
    mma16816z(c1, a[0], a[1], a[2], a[3], b2, b3);
    sts_v2(t1.z, fu((c0[0] + c1[2]) * SL2E), fu((c0[1] + c1[3]) * SL2E));
    if (NW > 0) bar_sync(B_S, 256); else bar_arrive(B_S, 256);
    stsm4t(kmd, kf);
    fence_async_smem();
    bar_arrive(B_KM, 256);
  };
  mbar_wait1(sb + K1_BAR + MB_X, 0);
#pragma unroll 1
  for (int s = 0; s < NSTEP; s++) {
    const uint32_t par = s & 1;
    uint32_t rk, rb;
    {
      auto mid1 = [&]() { if (s > 0) scores(s - 1); };
      uint4 t5, t0, kx[2];
      uint32_t bc, tgo;
      auto mid = [&]() {
        const int dq0 = max((int)lds_vol(tb + 16384) - DLY_DN, 0);
        t5 = tab(tb, 5); bc = t5.y ^ t5.x ^ t5.z;
        expect_e(bc, 1024); expect_e(bc + 32, 1024); expect_e(bc - 32, 512);
        if (NW1 + NW == 0) mbar_wait1(sb + K1_BAR + MB_X + 8 * par, (s >> 1) & 1);
        if (s > 0) bar_sync(B_GOX, 256);
        sts_v2(tb + 16384, dq0, clk() + dq0);
      };
      if (par) k_shadow<1>(wf, t5, bc, tb, t0, kx, tgo, mid1, mid); else k_shadow<0>(wf, t5, bc, tb, t0, kx, tgo, mid1, mid);
      const uint8_t* p0 = mkptr(t0.z ^ ((par ^ 1) << 20), t0.w);
      uint4 v[8];
      wait_until(tgo);
      int dq = 0;
#pragma unroll
      for (int i = 0; i < 8; i++) v[i] = (EXP == 2) ? make_uint4(tgo, i, tgo, i) : ld_rlx(p0 + (i & 3) * 512 + (i >> 2) * 16384);
      stsm4t(t5.w + 5120, kx[0]); stsm4t(t5.w + 5120 + 256, kx[1]);
      uint32_t at[8][4];
      proj2_pre<0>(at, t0.x);
      TS(15);
      if (s > 0) {
        repoll<8, 512>(v, p0, p0 + 16384, phase_of(s - 1), &dq);
#pragma unroll
        for (int i = 0; i < 4; i++) sts_v4(t0.y + i * 512, badd4(v[i], v[i + 4]));
      }
      TSA(4 + (threadIdx.x >> 5));
      if (KBAR) bar_sync(B_MEM, 256); else bar_arrive(B_MEM, 256);
      if (dq) asm volatile("red.shared.add.u32 [%0], %1;" ::"r"(tb + 16384), "r"(DLY_UP + DLY_DN) : "memory");
      const uint4 t3 = tab(tb, 3);
      if (KP1 == 1) proj2_pre<1>(at, t0.x);
      rk = t3.x; rb = t3.y;
      const uint32_t mems = KBAR ? sb + Q_MEMS + (t0.y & 511) : t3.z;
      TS(9);
      if (GOI > 0) bar_sync(B_GOK, 256); else if (!KBAR) bar_sync(B_GOK, 128);
      float k[8];
      proj2<0>(k, wf, at, t0.x, mems);
      kh = pack8<0>(k);
    }
    sta_u4(rk, kh.x, kh.y, kh.z, kh.w, rb);
    if (NW1 + NW > 0 && s + 1 < NSTEP) mbar_wait1(sb + K1_BAR + MB_X + 8 * (par ^ 1), ((s + 1) >> 1) & 1);
    if (NW1 > 0) bar_sync(B_PD, 256);
    TS(10);
  }
  scores(NSTEP - 1);
  bar_sync(B_GOX, 256);
  bar_sync(B_SX, 256);
}

template <int WG> __device__ __forceinline__ void role_v(uint32_t sb, const CUtensorMap* tmX, const bf16* __restrict__ Wo, const CUtensorMap* tmOx, uint8_t* __restrict__ xw, const bf16* __restrict__ mem0) {
  uint32_t vf[KR][4], of[2][OR][4];
  const uint32_t BAR = sb + K1_BAR;
  const int h = blockIdx.x >> 2, j = blockIdx.x & 1;
#pragma unroll
  for (int i = 0; i < KR; i++) asm volatile("" : "=r"(vf[i][0]), "=r"(vf[i][1]), "=r"(vf[i][2]), "=r"(vf[i][3]));
#pragma unroll
  for (int i = 0; i < 2 * OR; i++) asm volatile("" : "=r"(of[i & 1][i >> 1][0]), "=r"(of[i & 1][i >> 1][1]), "=r"(of[i & 1][i >> 1][2]), "=r"(of[i & 1][i >> 1][3]));
  if (!K1_DRY) {
    const int tid = threadIdx.x, lane = tid & 31, w = (tid >> 5) & 3, mi = lane >> 3, kr = (mi >> 1) * 8 + (lane & 7), g = lane >> 2, tq = lane & 3;
    const uint32_t lo = kr * 128 + (((2 * w + (mi & 1)) ^ (kr & 7)) << 4), pb = BAR + MB_P + WG * 32, stg = sb + V_STG + WG * 65536;
    const uint32_t wst = (w == 2) ? sb + V_XT + 32768 + WG * 16384 : stg + w * 16384;
    auto fetch_wo = [&]() {
      const bf16* gsrc = Wo + (size_t)(2048 * j + 1024 * WG + 256 * w + g) * DM + 32 * h + tq * 8;
#pragma unroll 8
      for (int i = 0; i < 32; i++) cp_async16(wst + (4 * i + (g >> 1)) * 128 + (((g ^ (g >> 2)) & 1) << 6) + tq * 16, gsrc + (size_t)(8 * i) * DM);
    };
    if (w >= 2) fetch_wo();
    mbar_wait1(pb, 0);
    TSG(2);
#pragma unroll
    for (int ks = 0; ks < KR; ks++) ldsm4t(vf[ks], stg + ks * 2048 + lo);
    bar_sync(B_W0 + WG, 128);
    if (w < 2) fetch_wo();
    asm volatile("cp.async.wait_all;" ::: "memory");
    __syncwarp();
    TSG(3);
    uint32_t tmp[2 * (16 - OR)][4];
    const uint32_t src = wst + (16 * (tq >> 1) + 4 * (tq & 1)) * 64 + g * 8, e = (tq & 1) << 6;
#pragma unroll
    for (int ks = 0; ks < 16; ks++) {
      const int pi = ks >> 1, si = (pi == 0) ? 0 : (pi == 3) ? 1 : (pi == 6) ? 2 : -1, ri = pi - 1 - (pi > 3) - (pi > 6);
      uint32_t (&f0)[4] = (si < 0) ? of[0][si < 0 ? 2 * ri + (ks & 1) : 0] : tmp[si < 0 ? 0 : 4 * si + 2 * (ks & 1)];
      uint32_t (&f1)[4] = (si < 0) ? of[1][si < 0 ? 2 * ri + (ks & 1) : 0] : tmp[si < 0 ? 0 : 4 * si + 2 * (ks & 1) + 1];
      const uint32_t a = src + (32 * pi + 2 * (ks & 1)) * 64;
      const float2 w0 = lds_f2(a + e), w1 = lds_f2(a + (e ^ 64)), w2 = lds_f2(a + 512 + e), w3 = lds_f2(a + 512 + (e ^ 64));
      f0[0] = prmt(fu(w0.x), fu(w1.x), 0x5410u); f0[1] = prmt(fu(w0.x), fu(w1.x), 0x7632u); f0[2] = prmt(fu(w2.x), fu(w3.x), 0x5410u); f0[3] = prmt(fu(w2.x), fu(w3.x), 0x7632u);
      f1[0] = prmt(fu(w0.y), fu(w1.y), 0x5410u); f1[1] = prmt(fu(w0.y), fu(w1.y), 0x7632u); f1[2] = prmt(fu(w2.y), fu(w3.y), 0x5410u); f1[3] = prmt(fu(w2.y), fu(w3.y), 0x7632u);
    }
    __syncwarp();
#pragma unroll
    for (int i = 0; i < 2 * (16 - OR); i++) sts_v4(stg + w * 16384 + i * 512 + lane * 16, make_uint4(tmp[i][0], tmp[i][1], tmp[i][2], tmp[i][3]));
    fence_async_smem();
  }
  TSG(4);
  cluster_sync_all();
  TSG(5);
  constexpr int T2 = WG ? 16384 - 2048 : -12288, T3 = T2 + 2048, T4 = -12288;
  uint32_t tb;
  {
    const int lane = threadIdx.x & 31, w = (threadIdx.x >> 5) & 3, warp = 4 * WG + w, mi = lane >> 3, r8 = lane & 7, kr = (mi >> 1) * 8 + r8, g = lane >> 2, tq = lane & 3;
    const uint32_t l16 = sb + lane * 16, side = my_side(BAR), t = sb + V_TAB + threadIdx.x * 16, ex = l16 + V_VXEX + w * 16384;
    sts_v4(t, make_uint4(w * 1024 + lane * 16 + side_off(XW_MEM + (j * 4 + WG) * 8192, side), XW_VM + (2 * h + (WG ^ j)) * 8192 + j * 2048 + w * 512 + lane * 16,
                         l16 + V_MEMS + warp * 1024, sb + V_WRES + WG * 16384 + kr * 128 + (((2 * w + (mi & 1)) ^ (kr & 7)) << 4)));
    sts_v4(t + 4096, make_uint4(side_off(XW_O + (8 * j + warp) * 8192, side) + lane * 16 + 2048,
                                XW_MEM + ((h >> 4) * 4 + j * 2 + ((h >> 3) & 1)) * 8192 + (h & 7) * 512 + w * 128 + r8 * 16 + (2 * (mi & 1) + (mi >> 1)) * 4,
                                l16 + V_STG + warp * 16384, sb + V_STG + V_RED + (mi >> 1) * 512 + w * 128 + (lane & 15) * 8));
    if (WG == 0) {
      sts_v4(t + T2, make_uint4(XW_VX + (2 * h + j) * 4096 + w * 1024 + lane * 16, l16 + V_VXS + w * 1024, ex, BAR + MB_A + 8 * w));
    } else {
      const int orow = 8 * (mi & 1) + r8;
      sts_v4(t + T2, make_uint4(mapa(ex, j ^ 1), mapa(BAR + MB_A + 8 * w, j ^ 1), l16 + V_VXS + w * 1024, l16 + V_PS));
      sts_v4(t + T3, make_uint4(XW_SX + 2 * h * 4096 + (w & 1) * 512 + lane * 16, l16 + V_PF + w * 16384, l16 + V_PS + (w >> 1) * 1536 + (w & 1) * 4, l16 + V_STG + w * 16384 + 7168));
      sts_v4(t + T4, make_uint4(XW_VM + (2 * h + j) * 8192 + w * 512 + lane * 16, sb + V_OX + orow * 128 + (((2 * w + (mi >> 1)) ^ r8) << 4), (w >> 1) * 1024, (6 + (w >> 1) - (w & 1)) * 512));
      const int lim = 8 * w + g - 2 * tq;
#pragma unroll
      for (int i = 0; i < 2; i++)
        sts_v4(l16 + V_STG + w * 16384 + 7168 + i * 512, make_uint4(16 * i > lim ? 0xff800000u : 0u, 16 * i + 1 > lim ? 0xff800000u : 0u, 16 * i + 8 > lim ? 0xff800000u : 0u, 16 * i + 9 > lim ? 0xff800000u : 0u));
    }
#pragma unroll
    for (int i = 0; i < 2; i++) sts_v4(l16 + V_MEMS + warp * 1024 + i * 512, ldg_nc_v4(mem0 + r8 * DM + j * 512 + (8 * warp + 4 * i + mi) * 8));
    tb = opaque(l16 + V_STG + warp * 16384 + V_RED, t);
  }
  TSG(6);
  auto store_ox = [&](int seg) {
    if (!K1_DRY)
      asm volatile("{\n.reg .pred p;\nelect.sync _|p, 0xffffffff;\n@p cp.async.bulk.tensor.2d.global.shared::cta.bulk_group [%0, {%2, %3}], [%1];\ncp.async.bulk.commit_group;\n}"
                   ::"l"(tmOx), "r"(sb + V_OX), "r"(h * DH + 64 * j), "r"(seg * SEG) : "memory");
  };
  uint32_t tpub = 0;
  int dd = DLY_V * 65536 + DLY_O;
#pragma unroll 1
  for (int s = -1; s <= NSTEP; s++) {
    const uint32_t ph = phase_of(s), slot = (s & 1) * XW_SLOT;
    const int n = s + 1, a = s - 1;
    const uint32_t pa = phase_of(a);
    uint32_t tm = 0;
    auto prefetch = [&]() {
      const uint4 t3 = tabo(tb + T3), t4 = tabo(tb + T4);
      const uint8_t* p0 = xw + (t3.x + (a & 1) * XW_SXS);
      const uint8_t* vp = xw + (t4.x + (slot ^ XW_SLOT));
#pragma unroll
      for (int p = 0; p < 2; p++) {
        cp_async16(t3.y + (4 * p) * 512, p0 + p * 4096 + t4.z); cp_async16(t3.y + (4 * p + 1) * 512, p0 + p * 4096 + 2 * t4.z);
        cp_async16(t3.y + (4 * p + 2) * 512, p0 + p * 4096 + t4.w); cp_async16(t3.y + (4 * p + 3) * 512, vp + p * 2048);
      }
    };
    if (WG == 1 && s >= NSTEP) prefetch();
    if (s >= 0 && s < NSTEP) {
      const uint4 t0 = tab(tb, 0);
      uint32_t at[8][4];
#pragma unroll
      for (int i = 0; i < 8; i++) ldsm4t(at[i], t0.w + i * 2048);
      uint8_t* vp = xw + (t0.y + slot);
      const uint32_t mems = sb + V_MEMS + (t0.z & 511);
      int failed = 0;
      if (s > 0) {
        const uint8_t* p0 = xw + (t0.x + (slot ^ XW_SLOT));
        SCHED();
        wait_until(tpub);
        uint4 v[4];
#pragma unroll
        for (int i = 0; i < 4; i++) v[i] = ld_rlx(p0 + (i & 1) * 512 + (i >> 1) * 16384);
        if (WG == 1) prefetch();
        repoll<4, 512>(v, p0, p0 + 16384, phase_of(s - 1), &failed);

#pragma unroll
        for (int i = 0; i < 2; i++) sts_v4(t0.z + i * 512, badd4(v[i], v[i + 2]));
      }
      bar_sync(B_MEM, 256);
      TSW(16, 0);
      {
        float acc[4][4];
        uint32_t b[3][4];
        ldsm4(b[0], mems + 12 * 512); ldsm4(b[1], mems + 13 * 512);
#pragma unroll
        for (int i = 0; i < 16; i++) {
          const int p = (i + 12) & 15;
          if (i + 2 < 16) ldsm4(b[(i + 2) % 3], mems + ((p + 2) & 15) * 512);
#pragma unroll
          for (int u = 0; u < 2; u++) {
            const int ks = 2 * p + u;
            const uint32_t (&a)[4] = (ks < KR) ? vf[ks < KR ? ks : 0] : at[ks < KR ? 0 : ks - KR];
            if (i < 2) mma16816z(acc[ks & 3], a[0], a[1], a[2], a[3], b[i % 3][2 * u], b[i % 3][2 * u + 1]);
            else mma16816(acc[ks & 3], a[0], a[1], a[2], a[3], b[i % 3][2 * u], b[i % 3][2 * u + 1]);
          }
        }
        const uint32_t c0 = tagw(fu((acc[0][0] + acc[1][0]) + (acc[2][0] + acc[3][0])), ph), c1 = fu((acc[0][1] + acc[1][1]) + (acc[2][1] + acc[3][1])),
                       c2 = fu((acc[0][2] + acc[1][2]) + (acc[2][2] + acc[3][2])), c3 = fu((acc[0][3] + acc[1][3]) + (acc[2][3] + acc[3][3]));
        st_rlx(vp, c0, c1, c2, c3); st_rlx(vp + 4096, c0, c1, c2, c3);
      }
      SCHED();
      dd += (failed ? DLY_UP : (dd >> 16) >= DLY_DN ? -DLY_DN : 0) * 65536;
      tm = clk() + (dd & 65535);
      TSW(17, 0);
    }
    if constexpr (WG == 0) {
      const uint4 t2 = tabo(tb + T2);
      if (s >= NSTEP) bar_sync(B_MEM, 256);
      if (__any_sync(0xffffffffu, t2.w == BAR + MB_A)) {
        if (s >= 2) store_ox(s - 2);
        if (n + 1 < NSTEP) load_x(sb, V_XT, tmX, n + 1, j);
        if (s >= 1) { asm volatile("cp.async.bulk.wait_group.read 0;" ::: "memory"); bar_arrive(B_P, 160); }
      }
      if (n < NSTEP) {
        expect_e(t2.w, 1024);
        mbar_wait1(BAR + MB_X + 8 * (n & 1), (n >> 1) & 1);
        uint8_t* xp = xw + (t2.x + (slot ^ XW_SLOT));
        const uint32_t vs = t2.y + (n % 3) * 16384;
        bar_sync(B_GOV, 256);
        if (n & 1) v0_shadow<1>(vf, t2.z, t2.w, xp, vs, phase_of(n)); else v0_shadow<0>(vf, t2.z, t2.w, xp, vs, phase_of(n));
      }
    } else {
      if (s >= NSTEP) bar_sync(B_MEM, 256);
      uint4 t3, v[8];
      float4 ba, bb;
      uint32_t rex, rb;
      auto fetch = [&]() {
        { const uint4 t2 = tabo(tb + T2); rex = t2.x; rb = t2.y; }
        t3 = tabo(tb + T3);
        asm volatile("cp.async.wait_all;" ::: "memory");
#pragma unroll
        for (int i = 0; i < 8; i++) v[i] = lds_v4(t3.y + i * 512);
        ba = lds_f4(t3.w); bb = lds_f4(t3.w + 512);
      };
      if (n < NSTEP) {
        mbar_wait1(BAR + MB_X + 8 * (n & 1), (n >> 1) & 1);
        if (n & 1) v1_shadow<1>(vf, rex, rb, fetch); else v1_shadow<0>(vf, rex, rb, fetch);
      } else fetch();
      if (s >= 1 && !NOATT) {
        const uint4 t2 = tabo(tb + T2);
        if (!tags_ok<8>(v, pa)) {
          const uint8_t* p0 = xw + (lds_vol(tb + T3) + (a & 1) * XW_SXS);
          const uint4 t4 = tabo(tb + T4);
          const uint8_t* vp = xw + (t4.x + (slot ^ XW_SLOT));
#pragma unroll 1
          for (int it = 0; it < POLL_MAX; it++) {
#pragma unroll
            for (int p = 0; p < 2; p++) {
              v[4 * p] = ld_rlx(p0 + p * 4096 + t4.z); v[4 * p + 1] = ld_rlx(p0 + p * 4096 + 2 * t4.z);
              v[4 * p + 2] = ld_rlx(p0 + p * 4096 + t4.w); v[4 * p + 3] = ld_rlx(vp + p * 2048);
            }
            if (tags_ok<8>(v, pa)) break;
          }
        }
#pragma unroll
        for (int i = 0; i < 8; i++) asm volatile("" : "+r"(v[i].x), "+r"(v[i].y), "+r"(v[i].z), "+r"(v[i].w));
        const uint32_t vm0 = pack_bf16(uf(v[3].x) + uf(v[7].x), uf(v[3].y) + uf(v[7].y)), vm1 = pack_bf16(uf(v[3].z) + uf(v[7].z), uf(v[3].w) + uf(v[7].w));
        const bool hf = t3.z & 4;
        float e[10] = {fmaf(uf(v[0].x) + uf(v[4].x), SL2E, ba.x), fmaf(uf(v[0].y) + uf(v[4].y), SL2E, ba.y), fmaf(uf(v[0].z) + uf(v[4].z), SL2E, ba.z), fmaf(uf(v[0].w) + uf(v[4].w), SL2E, ba.w),
                       fmaf(uf(v[1].x) + uf(v[5].x), SL2E, bb.x), fmaf(uf(v[1].y) + uf(v[5].y), SL2E, bb.y), fmaf(uf(v[1].z) + uf(v[5].z), SL2E, bb.z), fmaf(uf(v[1].w) + uf(v[5].w), SL2E, bb.w),
                       (uf(hf ? v[2].z : v[2].x) + uf(hf ? v[6].z : v[6].x)) * SL2E, (uf(hf ? v[2].w : v[2].y) + uf(hf ? v[6].w : v[6].y)) * SL2E};
        float mx = fmaxf(fmaxf(fmaxf(fmaxf(e[0], e[1]), fmaxf(e[2], e[3])), fmaxf(fmaxf(e[4], e[5]), fmaxf(e[6], e[7]))), fmaxf(e[8], e[9]));
        mx = fmaxf(mx, __shfl_xor_sync(0xffffffffu, mx, 1));
        mx = fmaxf(mx, __shfl_xor_sync(0xffffffffu, mx, 2));
        const uint32_t vs = t2.z + (a % 3) * 16384, oxs = lds_vol(tb + T4 + 4);
        const uint4 v0 = lds_v4(vs), v1 = lds_v4(vs + 512);
#pragma unroll
        for (int i = 0; i < 10; i++) e[i] = ex2(e[i] - mx);
        float sum = ((e[0] + e[1]) + (e[2] + e[3])) + ((e[4] + e[5]) + (e[6] + e[7])) + (e[8] + e[9]);
        sum += __shfl_xor_sync(0xffffffffu, sum, 1);
        sum += __shfl_xor_sync(0xffffffffu, sum, 2);
        const float inv = rcp(sum);
#pragma unroll
        for (int i = 0; i < 5; i++) sts_u32(t3.z + (i >> 1) * 512 + (i & 1) * 8, pack_bf16(e[2 * i] * inv, e[2 * i + 1] * inv));
        bar_sync(B_P, 160);
        uint4 q[5];
#pragma unroll
        for (int i = 0; i < 5; i++) q[i] = lds_v4(t2.w + (i + (i > 0)) * 512);
        float c[4][4];
        mma16816z(c[2], q[2].x, q[2].y, q[2].z, q[2].w, v0.x, v0.y); mma16816z(c[3], q[2].x, q[2].y, q[2].z, q[2].w, v1.x, v1.y);
        mma16816z(c[0], q[0].x, q[0].y, q[0].z, q[0].w, v0.x, v0.y); mma16816z(c[1], q[0].x, q[0].y, q[0].z, q[0].w, v1.x, v1.y);
        mma16816(c[2], q[3].x, q[3].y, q[3].z, q[3].w, v0.z, v0.w); mma16816(c[3], q[3].x, q[3].y, q[3].z, q[3].w, v1.z, v1.w);
        mma1688(c[0], q[1].x, q[1].y, vm0); mma1688(c[1], q[1].x, q[1].y, vm1);
        mma1688(c[2], q[4].x, q[4].y, vm0); mma1688(c[3], q[4].x, q[4].y, vm1);
#pragma unroll
        for (int m = 0; m < 2; m++)
          asm volatile("stmatrix.sync.aligned.m8n8.x4.shared.b16 [%0], {%1,%2,%3,%4};" ::"r"(oxs + m * 2048), "r"(pack_bf16(c[2 * m][0], c[2 * m][1])), "r"(pack_bf16(c[2 * m][2], c[2 * m][3])),
                       "r"(pack_bf16(c[2 * m + 1][0], c[2 * m + 1][1])), "r"(pack_bf16(c[2 * m + 1][2], c[2 * m + 1][3])) : "memory");
      }
    }
    TSW(19, 0); TSW(20, 4);
    if (s < 0) TSG(7);
    if (TAILSKIP && WG == 0 && s == NSTEP - 1) {
      uint8_t* mp = xw + (lds_vol(tb + 4096 + 4) + slot);
      st_rlx32(mp, ph); st_rlx32(mp + 4096, ph);
    }
    if (s >= 0 && s < NSTEP - TAILSKIP) {
      const uint4 t1 = tab(tb, 1);
      const uint8_t* op = xw + (t1.x + slot) - 2048;
      const uint32_t wo = t1.z;
      uint4 at[4];
#pragma unroll
      for (int i = 0; i < 4; i++) at[i] = lds_v4(wo + i * 512);
      uint8_t* mp = xw + (t1.y + slot);
      const uint32_t tsel = (t1.y & 12) ? 0u : 1u;
      SCHED();
      wait_until(tm);
      TSW(22, 0);
      int nmiss = 0;
      uint4 o[8];
#pragma unroll
      for (int i = 0; i < 8; i++) o[i] = ld_rlx(op + i * 512);
      auto wo_mma = [&]() -> uint32_t {
        float acc[2][2][4];
        uint32_t late = 0;
#pragma unroll
        for (int i = 0; i < 8; i++) {
          const int si = (i == 0) ? 0 : (i == 3) ? 1 : (i == 6) ? 2 : -1, ri = i - 1 - (i > 3) - (i > 6);
          if (i == 7) late = fu(acc[0][0][0]);
#pragma unroll
          for (int u = 0; u < 2; u++)
#pragma unroll
            for (int mt = 0; mt < 2; mt++) {
              const uint32_t b0 = u ? o[i].z : o[i].x, b1 = u ? o[i].w : o[i].y;
              if (si < 0) mma16816(acc[mt][u], of[mt][si < 0 ? 2 * ri + u : 0][0], of[mt][si < 0 ? 2 * ri + u : 0][1], of[mt][si < 0 ? 2 * ri + u : 0][2], of[mt][si < 0 ? 2 * ri + u : 0][3], b0, b1);
              else {
                const uint4 a = at[2 * u + mt];
                if (i == 0) mma16816z(acc[mt][u], a.x, a.y, a.z, a.w, b0, b1); else mma16816(acc[mt][u], a.x, a.y, a.z, a.w, b0, b1);
                if (si < 2) at[2 * u + mt] = lds_v4(wo + (4 * (si + 1) + 2 * u + mt) * 512);
              }
            }
        }
#pragma unroll
        for (int mt = 0; mt < 2; mt++)
          sts_f4(wo + V_RED + mt * 512, acc[mt][0][0] + acc[mt][1][0], acc[mt][0][2] + acc[mt][1][2], acc[mt][0][1] + acc[mt][1][1], acc[mt][0][3] + acc[mt][1][3]);
        return late;
      };
      {
        uint32_t phl;
        asm volatile("lop3.b32 %0, %1, %2, %3, 0xf8;" : "=r"(phl) : "r"(ph), "r"(wo_mma()), "r"(wo));
        if (!tags_ok<8>(o, phl)) {
          nmiss = 1;
          repoll<8, 512>(o, op, op + 2048, ph);
#pragma unroll
          for (int i = 0; i < 4; i++) at[i] = lds_v4(wo + i * 512);
          wo_mma();
        }
      }
      TSA(8 + (threadIdx.x >> 5));
      if constexpr (WG == 1) bar_arrive(B_RED, 256);
      if constexpr (WG == 0) {
        bar_sync(B_RED, 256);
        float2 r[8];
#pragma unroll
        for (int i = 0; i < 8; i++) r[i] = lds_f2(t1.w + i * 16384);
        const uint32_t mw = (pack_bf16(((r[0].x + r[1].x) + (r[2].x + r[3].x)) + ((r[4].x + r[5].x) + (r[6].x + r[7].x)),
                                       ((r[0].y + r[1].y) + (r[2].y + r[3].y)) + ((r[4].y + r[5].y) + (r[6].y + r[7].y))) & ~tsel) | (tsel & ph);
        st_rlx32(mp, mw); st_rlx32(mp + 4096, mw);
      }
      SCHED();
      if (WG == 0) TSA(2 + (threadIdx.x >> 5));
      dd += nmiss ? DLY_UP : (dd & 65535) >= DLY_DN ? -DLY_DN : 0;
      tpub = clk() + (dd >> 16);
      TSW(23, 0);
    }
    if (WG == 1) fence_async_smem();
  }
  bar_sync(B_MEM, 256);
  if (WG == 0 && threadIdx.x < 32) { store_ox(NSTEP - 1); asm volatile("cp.async.bulk.wait_group 0;" ::: "memory"); }
}

__global__ void __cluster_dims__(2, 1, 1) __launch_bounds__(256, 1)
k1_rec(const __grid_constant__ CUtensorMap tmX, const __grid_constant__ CUtensorMap tmWq, const __grid_constant__ CUtensorMap tmWk,
       const __grid_constant__ CUtensorMap tmWv, const __grid_constant__ CUtensorMap tmOx, uint8_t* __restrict__ xw, const bf16* __restrict__ mem0, const bf16* Wo) {
  extern __shared__ __align__(1024) uint8_t smem[];
  const uint32_t sb = smem_u32(smem);
  if ((sb & 0xFFFFFFu) != SMEM0) __trap();
  {
    const int tid = threadIdx.x, wg = tid >> 7, cta = blockIdx.x, h = cta >> 2, j = cta & 1;
    const uint32_t BAR = sb + K1_BAR;
    if (tid == 0) {
      mbar_init(BAR + MB_X, 1); mbar_init(BAR + MB_X + 8, 1); mbar_init(BAR + MB_S, 5);
      for (int i = 0; i < 24; i++) mbar_init(BAR + MB_A + 8 * i, 1);
      asm volatile("fence.mbarrier_init.release.cluster;" ::: "memory");
    }
    if (tid >= 64 && tid < 128) {
      bar_arrive(0, 256);
      if ((tid & 31) == 0) sts_u32(BAR + 240 + ((tid >> 3) & 4), probe_rtt(xw, BAR + 248 + ((tid >> 3) & 4), (tid >> 5) & 1));
      __syncwarp();
      bar_sync(15, 96);
    } else {
      bar_sync(0, 256);
      if (tid < 32) bar_arrive(15, 96);
    }
    TSG(16);
#define WPF 0
    if (WPF && tid >= 64 && tid < 68 && !K1_DRY)
      asm volatile("cp.async.bulk.prefetch.L2.global [%0], %1;" ::"l"(Wo + (size_t)cta * 32768 + (tid & 3) * 8192), "r"(16384) : "memory");
    if (tid == 96) asm volatile("prefetch.global.L2 [%0];" ::"l"(mem0 + cta * 64) : "memory");
    if ((tid & 127) == 0 && !K1_DRY) {
      const uint32_t pb = BAR + MB_P + wg * 32;
      if (!(cta & 2)) {
        const CUtensorMap* tm = wg ? &tmWk : &tmWq;
        for (int c = 0; c < 2; c++) {
          mbar_expect_tx(pb + 8 * c, 32768);
          for (int t = 0; t < 2; t++) tma_load_2d(sb + Q_STG + wg * 65536 + (2 * c + t) * 16384, tm, h * DH + 64 * t, j * 512 + 128 * c, pb + 8 * c);
        }
        mbar_expect_tx(pb + 24, 32768);
        for (int t = 0; t < 2; t++) tma_load_2d(sb + Q_WRES + wg * 32768 + t * 16384, tm, h * DH + 64 * t, j * 512 + 384, pb + 24);
      } else {
        mbar_expect_tx(pb, 65536);
        for (int c = 0; c < 3; c++) tma_load_2d(sb + V_STG + wg * 65536 + c * 16384, &tmWv, h * DH + 64 * (wg ^ j), j * 512 + 128 * c, pb);
        tma_load_2d(sb + V_WRES + wg * 16384, &tmWv, h * DH + 64 * (wg ^ j), j * 512 + 384, pb);
      }
    }
    __syncwarp();
    if (tid < 32) load_x(sb, (cta & 2) ? V_XT : Q_XT, &tmX, 0, j);
  }
  const int role = __shfl_sync(0xffffffffu, (threadIdx.x >> 7) | (blockIdx.x & 2), 0);
  if (role == 0) role_q(sb, &tmX, &tmWq, xw);
  else if (role == 1) role_k(sb, &tmWk, xw, mem0);
  else if (role == 2) role_v<0>(sb, &tmX, Wo, &tmOx, xw, mem0);
  else role_v<1>(sb, &tmX, Wo, &tmOx, xw, mem0);
  asm volatile("griddepcontrol.launch_dependents;" ::: "memory");
  TS_DUMP();
  TSG(29);
}

constexpr int G_STAGES = 5;
constexpr int G_STAGE_BYTES = 32768;
constexpr int G_SMEM = (G_STAGES + 2) * G_STAGE_BYTES + 1024 + 256;

template <int EPI>
__global__ void __launch_bounds__(544, 1)
k2_gemm(const __grid_constant__ CUtensorMap tmA, const __grid_constant__ CUtensorMap tmB, const __grid_constant__ CUtensorMap tmY,
        const __grid_constant__ CUtensorMap tmQ, const __grid_constant__ CUtensorMap tmOut, const __grid_constant__ CUtensorMap tmYo,
        const bf16* __restrict__ ssm_k, const bf16* __restrict__ ssm_D, int kblocks) {
  extern __shared__ uint8_t smem_raw[];
  const uint32_t sb = (smem_u32(smem_raw) + 1023) & ~1023u;
  const uint32_t ysm = sb + G_STAGES * G_STAGE_BYTES;
  const uint32_t qsm = ysm + G_STAGE_BYTES;
  const uint32_t bars = qsm + G_STAGE_BYTES;
  const int tid = threadIdx.x, warp = __shfl_sync(0xffffffffu, tid >> 5, 0), lane = tid & 31;
  const int n0 = blockIdx.x * 128, m0 = blockIdx.y * 128;
#define TS2(i)
#define TS3(i)
  TS2(30);
  if (tid == 0) {
    for (int s = 0; s < G_STAGES; s++) { mbar_init(bars + 8 * s, 1); mbar_init(bars + 64 + 8 * s, 2); }
    mbar_init(bars + 128, 2);
    asm volatile("fence.mbarrier_init.release.cluster;" ::: "memory");
  }
  __syncthreads();
  if (warp == 16) {
    if (lane == 0) {
      int st = 0; uint32_t ph = 1;
      for (int s = 0; s < G_STAGES; s++) {
        mbar_expect_tx(bars + 8 * s, G_STAGE_BYTES);
        tma_load_2d(sb + s * G_STAGE_BYTES + 16384, &tmB, n0, s * 64, bars + 8 * s);
        tma_load_2d(sb + s * G_STAGE_BYTES + 24576, &tmB, n0 + 64, s * 64, bars + 8 * s);
      }
      asm volatile("griddepcontrol.wait;" ::: "memory");
      for (int kb = 0; kb < kblocks; kb++) {
        const uint32_t dst = sb + st * G_STAGE_BYTES, fb = bars + 8 * st;
        if (kb >= G_STAGES) {
          mbar_wait(bars + 64 + 8 * st, ph);
          mbar_expect_tx(fb, G_STAGE_BYTES);
          tma_load_2d(dst + 16384, &tmB, n0, kb * 64, fb);
          tma_load_2d(dst + 24576, &tmB, n0 + 64, kb * 64, fb);
        }
        tma_load_2d(dst, &tmA, kb * 64, m0, fb);
        if (++st == G_STAGES) { st = 0; ph ^= 1; }
      }
    }
  } else if (warp >= 8) {
    const int cw = (warp >> 2) & 1;
    if ((tid & 127) == 0 && KC_BG + cw * 128 < DM) wait_count(&g_ka_done, 4);
    conv_wg<1>(ysm + cw * G_STAGE_BYTES, 2 + cw, KC_BG + cw * 128 + blockIdx.y * gridDim.x + blockIdx.x, 256, DM, &tmYo, ssm_k, ssm_D);
    TS3(26);
    if (tid == 256) {
      wait_count(&g_conv_done, DM);
      mbar_expect_tx(bars + 128, 32768);
      tma_load_2d(ysm, &tmY, m0, n0, bars + 128);
      tma_load_2d(ysm + 16384, &tmY, m0 + 64, n0, bars + 128);
      if (atomicAdd(&g_k2_seen, 1) == 127) { g_ka_done = 0; g_conv_done = 0; g_k2_seen = 0; }
    } else if (tid == 384) {
      mbar_expect_tx(bars + 128, 32768);
      tma_load_2d(qsm, &tmQ, n0, m0, bars + 128);
      tma_load_2d(qsm + 16384, &tmQ, n0 + 64, m0, bars + 128);
    }
  } else {
    const int wg = warp >> 2;
    float acc[64];
    int st = 0; uint32_t ph = 0;
    for (int kb = 0; kb < kblocks; kb++) {
      mbar_wait(bars + 8 * st, ph);
      const uint32_t a = sb + st * G_STAGE_BYTES + wg * 8192, b = sb + st * G_STAGE_BYTES + 16384;
      const uint64_t da = make_desc(a, 16, 1024, 1), db = make_desc(b, 8192, 1024, 1);
      wg_fence();
#pragma unroll
      for (int ks = 0; ks < 4; ks++) wg_ss_n128_tb<0>(acc, da + ks * 2, db + ks * 128, (kb | ks) != 0);
      wg_commit();
      wg_wait<1>();
      if (kb > 0) {
        const int ps = (st == 0) ? G_STAGES - 1 : st - 1;
        if ((tid & 127) == 0) mbar_arrive(bars + 64 + 8 * ps);
      }
      if (++st == G_STAGES) { st = 0; ph ^= 1; }
    }
    wg_wait<0>(); fence_regs(acc);
    TS2(27);
    const int g = lane >> 2;
    const int rl = wg * 64 + (warp & 3) * 16;
    mbar_wait(bars + 128, 0);
    const float gt0 = __ldcg(g_gate + m0 + rl + g), gt1 = __ldcg(g_gate + m0 + rl + g + 8);
    const float om0 = rbf(1.f - gt0), om1 = rbf(1.f - gt1);
    const int mi = lane >> 3, tc = wg * 8 + (warp & 3) * 2 + (mi & 1);
    const int qr = rl + 8 * (mi & 1) + (lane & 7);
#pragma unroll
    for (int j2 = 0; j2 < 8; j2++) {
      const int d = 16 * j2 + 8 * (mi >> 1) + (lane & 7);
      uint32_t yf[4], qf[4], of[4];
      asm volatile("ldmatrix.sync.aligned.m8n8.x4.trans.shared.b16 {%0,%1,%2,%3}, [%4];" : "=r"(yf[0]), "=r"(yf[1]), "=r"(yf[2]), "=r"(yf[3])
                   : "r"(ysm + (tc >> 3) * 16384 + d * 128 + (((tc & 7) ^ (d & 7)) << 4)) : "memory");
      const int cc = 2 * j2 + (mi >> 1);
      const uint32_t qa = qsm + (cc >> 3) * 16384 + qr * 128 + (((cc & 7) ^ (qr & 7)) << 4);
      asm volatile("ldmatrix.sync.aligned.m8n8.x4.shared.b16 {%0,%1,%2,%3}, [%4];" : "=r"(qf[0]), "=r"(qf[1]), "=r"(qf[2]), "=r"(qf[3]) : "r"(qa) : "memory");
#pragma unroll
      for (int jj = 0; jj < 2; jj++)
#pragma unroll
        for (int hf = 0; hf < 2; hf++) {
          const int j = 2 * j2 + jj;
          const float gt = hf ? gt1 : gt0, om = hf ? om1 : om0;
          const uint32_t aw = bmul2(qf[2 * jj + hf], yf[2 * jj + hf]);
          const uint32_t bw = pack_bf16(acc[4 * j + 2 * hf], acc[4 * j + 2 * hf + 1]);
          of[2 * jj + hf] = badd2(pack_bf16(gt * bf_lo(aw), gt * bf_hi(aw)), pack_bf16(om * bf_lo(bw), om * bf_hi(bw)));
        }
      asm volatile("stmatrix.sync.aligned.m8n8.x4.shared.b16 [%0], {%1,%2,%3,%4};" ::"r"(qa), "r"(of[0]), "r"(of[1]), "r"(of[2]), "r"(of[3]) : "memory");
    }
    fence_async_smem();
    bar_sync(1, 256);
    if (tid == 0) {
      asm volatile("cp.async.bulk.tensor.2d.global.shared::cta.bulk_group [%0, {%2, %3}], [%1];" ::"l"(&tmOut), "r"(qsm), "r"(n0), "r"(m0) : "memory");
      asm volatile("cp.async.bulk.tensor.2d.global.shared::cta.bulk_group [%0, {%2, %3}], [%1];" ::"l"(&tmOut), "r"(qsm + 16384), "r"(n0 + 64), "r"(m0) : "memory");
      asm volatile("cp.async.bulk.commit_group;\ncp.async.bulk.wait_group 0;" ::: "memory");
    }
    TS2(31);
  }
}

typedef CUresult (*PFN_encodeTiled)(CUtensorMap*, CUtensorMapDataType, cuuint32_t, void*, const cuuint64_t*, const cuuint64_t*,
                                    const cuuint32_t*, const cuuint32_t*, CUtensorMapInterleave, CUtensorMapSwizzle,
                                    CUtensorMapL2promotion, CUtensorMapFloatOOBfill);
static PFN_encodeTiled get_encode() {
  static PFN_encodeTiled fn = nullptr;
  if (!fn) {
    void* p = nullptr; cudaDriverEntryPointQueryResult st;
    cudaGetDriverEntryPoint("cuTensorMapEncodeTiled", &p, cudaEnableDefault, &st);
    fn = (PFN_encodeTiled)p;
  }
  return fn;
}
static CUtensorMap make_tm(const void* ptr, uint64_t rows, uint64_t cols, uint32_t brows, uint32_t bcols, CUtensorMapSwizzle swz = CU_TENSOR_MAP_SWIZZLE_128B) {
  CUtensorMap tm;
  cuuint64_t dims[2] = {cols, rows};
  cuuint64_t strides[1] = {cols * 2};
  cuuint32_t box[2] = {bcols, brows};
  cuuint32_t es[2] = {1, 1};
  get_encode()(&tm, CU_TENSOR_MAP_DATA_TYPE_BFLOAT16, 2, const_cast<void*>(ptr), dims, strides, box, es, CU_TENSOR_MAP_INTERLEAVE_NONE,
               swz, CU_TENSOR_MAP_L2_PROMOTION_L2_256B, CU_TENSOR_MAP_FLOAT_OOB_FILL_NONE);
  return tm;
}
static CUtensorMap make_tm_x(const void* ptr) {
  CUtensorMap tm;
  cuuint64_t dims[3] = {64, (cuuint64_t)SEQ, 16};
  cuuint64_t strides[2] = {DM * 2, 128};
  cuuint32_t box[3] = {64, SEG, 8};
  cuuint32_t es[3] = {1, 1, 1};
  get_encode()(&tm, CU_TENSOR_MAP_DATA_TYPE_BFLOAT16, 3, const_cast<void*>(ptr), dims, strides, box, es, CU_TENSOR_MAP_INTERLEAVE_NONE,
               CU_TENSOR_MAP_SWIZZLE_128B, CU_TENSOR_MAP_L2_PROMOTION_L2_256B, CU_TENSOR_MAP_FLOAT_OOB_FILL_NONE);
  return tm;
}
static CUtensorMap make_tm_kv(const void* ptr) {
  CUtensorMap tm;
  cuuint64_t dims[4] = {(cuuint64_t)DM, 2, (cuuint64_t)SEQ / 32, 16};
  cuuint64_t strides[3] = {DM * 2, DM * 2 * 32, DM * 2 * 2};
  cuuint32_t box[4] = {64, 2, 4, 16};
  cuuint32_t es[4] = {1, 1, 1, 1};
  get_encode()(&tm, CU_TENSOR_MAP_DATA_TYPE_BFLOAT16, 4, const_cast<void*>(ptr), dims, strides, box, es, CU_TENSOR_MAP_INTERLEAVE_NONE,
               CU_TENSOR_MAP_SWIZZLE_128B, CU_TENSOR_MAP_L2_PROMOTION_L2_256B, CU_TENSOR_MAP_FLOAT_OOB_FILL_NONE);
  return tm;
}
template <typename T> static T* sym_addr(T& sym) { void* p = nullptr; cudaGetSymbolAddress(&p, sym); return (T*)p; }

#define RUN(bit) true

#define K2_PDL 1
extern "C" void kernel_launch(void* const* d_in, const int* in_sizes, int n_in, void* d_out, int out_size) {
  const bf16* q = (const bf16*)d_in[0];
  const bf16* k = (const bf16*)d_in[1];
  const bf16* v = (const bf16*)d_in[2];
  const bf16* shift_k = (const bf16*)d_in[3];
  const bf16* ssm_k = (const bf16*)d_in[4];
  const bf16* ssm_D = (const bf16*)d_in[5];
  const bf16* mem0 = (const bf16*)d_in[7];
  const bf16* Wq = (const bf16*)d_in[8];
  const bf16* Wk = (const bf16*)d_in[9];
  const bf16* Wv = (const bf16*)d_in[10];
  const bf16* Wo = (const bf16*)d_in[11];
  const bf16* gate_w = (const bf16*)d_in[13];
  bf16* out = (bf16*)d_out;
  cudaStream_t st = cudaStreamPerThread;
  static cudaStream_t st2 = nullptr;
  static cudaEvent_t ev0 = nullptr, ev2 = nullptr;
  if (!st2) {
    cudaStreamCreateWithFlags(&st2, cudaStreamNonBlocking);
    cudaEventCreateWithFlags(&ev0, cudaEventDisableTiming);
    cudaEventCreateWithFlags(&ev2, cudaEventDisableTiming);
    cudaFuncSetAttribute(ka_prep, cudaFuncAttributeMaxDynamicSharedMemorySize, KA_SMEM);
    cudaFuncSetAttribute(kc_conv, cudaFuncAttributeMaxDynamicSharedMemorySize, KC_SMEM);
    cudaFuncSetAttribute(k1_rec, cudaFuncAttributeMaxDynamicSharedMemorySize, K1_SMEM);
    cudaFuncSetAttribute(k2_gemm<1>, cudaFuncAttributeMaxDynamicSharedMemorySize, G_SMEM);
  }
  void* ox = nullptr; cudaGetSymbolAddress(&ox, g_ox);
  void* y2 = nullptr; cudaGetSymbolAddress(&y2, g_y2T);
  CUtensorMap tmO = make_tm(ox, SEQ, HD, 128, 64);
  CUtensorMap tmWo = make_tm(Wo, HD, DM, 64, 64);
  CUtensorMap tmX = make_tm_x(q);
  CUtensorMap tmY = make_tm(y2, DM, SEQ, 128, 64);
  CUtensorMap tmQ = make_tm(q, SEQ, DM, 128, 64);
  CUtensorMap tmOut = make_tm(out, SEQ, DM, 128, 64);
  CUtensorMap tmWq = make_tm(Wq, DM, HD, 128, 64), tmWk = make_tm(Wk, DM, HD, 128, 64), tmWv = make_tm(Wv, DM, HD, 128, 64);
  CUtensorMap tmOx = make_tm(ox, SEQ, HD, 32, 64);
  CUtensorMap tmYo = make_tm(y2, (uint64_t)DM * 64, 32, 64, 32, CU_TENSOR_MAP_SWIZZLE_64B);
  CUtensorMap tmK = make_tm_kv(k), tmV = make_tm_kv(v);
  void* xw = nullptr; cudaGetSymbolAddress(&xw, g_xw);
  xw = (void*)(((uintptr_t)xw + (2u << 20) - 1) & ~(uintptr_t)((2u << 20) - 1));
  cudaEventRecord(ev0, st);
  cudaStreamWaitEvent(st2, ev0, 0);
  if (RUN(4)) k1_rec<<<128, 256, K1_SMEM, st>>>(tmX, tmWq, tmWk, tmWv, tmOx, (uint8_t*)xw, mem0, Wo);
  if (RUN(4)) k1_rec<<<4, 256, K1_SMEM, st2>>>(tmX, tmWq, tmWk, tmWv, tmOx, (uint8_t*)xw + XW_DRY, mem0, Wo);
  if (RUN(1)) ka_prep<<<4, 512, KA_SMEM, st2>>>(tmK, tmV, q, gate_w, shift_k);
  if (RUN(16)) kc_conv<<<4, 512, KC_SMEM, st2>>>(tmYo, ssm_k, ssm_D);
  if (RUN(8)) {
    cudaLaunchConfig_t cfg = {};
    cfg.gridDim = dim3(DM / 128, SEQ / 128); cfg.blockDim = dim3(544); cfg.dynamicSmemBytes = G_SMEM; cfg.stream = st;
    cudaLaunchAttribute at[1];
    at[0].id = cudaLaunchAttributeProgrammaticStreamSerialization; at[0].val.programmaticStreamSerializationAllowed = K2_PDL;
    cfg.attrs = at; cfg.numAttrs = 1;
    cudaLaunchKernelEx(&cfg, k2_gemm<1>, tmO, tmWo, tmY, tmQ, tmOut, tmYo, ssm_k, ssm_D, HD / 64);
  }
  cudaEventRecord(ev2, st2);
  cudaStreamWaitEvent(st, ev2, 0);
}
```
